```python
import torch

def _softmax(x, axis=-1):
    return torch.softmax(x, dim=axis)
def _gelu(x):
    return torch.nn.functional.gelu(x, approximate="tanh")
def _silu(x):
    return torch.nn.functional.silu(x)
def _sigmoid(x):
    return torch.sigmoid(x)
def _layernorm(x, axis=-1, eps=1e-5):
    m = x.mean(dim=axis, keepdim=True)
    v = x.var(dim=axis, keepdim=True, unbiased=False)
    return (x - m) / torch.sqrt(v + eps)
def _scatter_add(tgt, idx, src, axis=0):
    return tgt.clone().index_add_(axis, idx, src)
def _segment_sum(src, seg, n):
    out = torch.zeros((n,) + src.shape[1:], dtype=src.dtype)
    return out.index_add_(0, seg, src)
def _pad(x, pw):
    flat = tuple(v for pair in reversed(pw) for v in pair)
    return torch.nn.functional.pad(x, flat)

kernel_name = 'recurrent_scan__linear_attn_block__glu_gated_swiglu__prompt'

def setup_inputs():

    _w = (lambda a: (lambda t: t.to(torch.bfloat16) if t.is_floating_point() else t)(torch.as_tensor(a)))
    def _A_setup():
        B, S, D = 1, 2048, 448
        return {
            "x": _w((lambda *s: torch.randn(*s, dtype=torch.bfloat16) * 0.05)(B, S, D)),
            "wqkv": _w((lambda *s: torch.randn(*s, dtype=torch.bfloat16) * 0.8)(D, 3 * D)),
            "wo": _w((lambda *s: torch.randn(*s, dtype=torch.bfloat16) * 0.8)(D, D)),
        }
    _A_in = _A_setup()

    def _B_setup():
        B, S, D, F = 1, 2048, 448, 1792
        return {
            "x": _w((lambda *s: torch.randn(*s, dtype=torch.bfloat16) * 0.05)(B, S, D)),
            "w1": _w((lambda *s: torch.randn(*s, dtype=torch.bfloat16) * 0.2)(D, F) * (2.0 / D) ** 0.5),
            "w3": _w((lambda *s: torch.randn(*s, dtype=torch.bfloat16) * 0.2)(D, F) * (2.0 / D) ** 0.5),
            "w2": _w((lambda *s: torch.randn(*s, dtype=torch.bfloat16) * 0.2)(F, D) * (2.0 / F) ** 0.5),
        }
    _B_in = _B_setup()

    return {
        "A_x": _A_in["x"],
        "A_wqkv": _A_in["wqkv"],
        "A_wo": _A_in["wo"],
        "B_x": _B_in["x"],
        "B_w1": _B_in["w1"],
        "B_w3": _B_in["w3"],
        "B_w2": _B_in["w2"],
    }

def reference(A_x, A_wqkv, A_wo, B_x, B_w1, B_w3, B_w2):
    def _A_ref(x, wqkv, wo):
        B, S, D = x.shape
        H = 16; Dh = D // H
        qkv = (lambda x, *d: x.permute(*d))((x @ wqkv).reshape(B, S, 3, H, Dh), 2, 0, 3, 1, 4)
        q, k, v = qkv[0], qkv[1], qkv[2]
        phi = lambda t: torch.where(t > 0, t + 1, torch.exp(t)) + 1e-6
        pq, pk = phi(q), phi(k)
        kv = torch.einsum("bhsd,bhse->bhde", pk, v)
        z = torch.einsum("bhsd->bhd", pk)
        num = torch.einsum("bhqd,bhde->bhqe", pq, kv)
        den = torch.einsum("bhqd,bhd->bhq", pq, z)[..., None] + 1e-6
        o = num / den
        return (lambda x, *d: x.permute(*d))(o, 0, 2, 1, 3).reshape(B, S, D) @ wo

    def _B_ref(x, w1, w3, w2):
        gate = torch.einsum("bsd,df->bsf", x, w1)
        up = torch.einsum("bsd,df->bsf", x, w3)
        h = _silu(gate) * up
        out = torch.einsum("bsf,fd->bsd", h, w2)
        return out

    x = A_x
    xn = _layernorm(x, axis=-1)
    s = _A_ref(xn, A_wqkv, A_wo)
    g = _silu(_B_ref(xn, B_w1, B_w3, B_w2))
    return x + s * g
```

```cpp
#include <cuda_runtime.h>
#include <cuda.h>
#include <cuda_bf16.h>
#include <stdint.h>
#include <type_traits>

template <int OFF, uint32_t HI, int SC> __device__ __forceinline__ void wgmma_rs_n56(float (&d)[28], uint32_t a0, uint32_t a1, uint32_t a2, uint32_t a3, uint32_t b) {
  asm volatile("{\n.reg .pred p;\n.reg .b32 lo;\n.reg .b64 db;\nsetp.ne.b32 p, %35, 0;\nadd.u32 lo, %32, %33;\nmov.b64 db, {lo, %34};\n"
    "wgmma.mma_async.sync.aligned.m64n56k16.f32.bf16.bf16 {%0, %1, %2, %3, %4, %5, %6, %7, %8, %9, %10, %11, %12, %13, %14, %15, %16, %17, %18, %19, %20, %21, %22, %23, %24, %25, %26, %27}, {%28, %29, %30, %31}, db, p, 1, 1, 1;\n}\n"
    : "+f"(d[0]), "+f"(d[1]), "+f"(d[2]), "+f"(d[3]), "+f"(d[4]), "+f"(d[5]), "+f"(d[6]), "+f"(d[7]), "+f"(d[8]), "+f"(d[9]), "+f"(d[10]), "+f"(d[11]), "+f"(d[12]), "+f"(d[13]), "+f"(d[14]), "+f"(d[15]), "+f"(d[16]), "+f"(d[17]), "+f"(d[18]), "+f"(d[19]), "+f"(d[20]), "+f"(d[21]), "+f"(d[22]), "+f"(d[23]), "+f"(d[24]), "+f"(d[25]), "+f"(d[26]), "+f"(d[27])
    : "r"(a0), "r"(a1), "r"(a2), "r"(a3), "r"(b), "n"(OFF), "n"(HI), "n"(SC));
}
template <int OFF, uint32_t HI, int SC> __device__ __forceinline__ void wgmma_rs_n64(float (&d)[32], uint32_t a0, uint32_t a1, uint32_t a2, uint32_t a3, uint32_t b) {
  asm volatile("{\n.reg .pred p;\n.reg .b32 lo;\n.reg .b64 db;\nsetp.ne.b32 p, %39, 0;\nadd.u32 lo, %36, %37;\nmov.b64 db, {lo, %38};\n"
    "wgmma.mma_async.sync.aligned.m64n64k16.f32.bf16.bf16 {%0, %1, %2, %3, %4, %5, %6, %7, %8, %9, %10, %11, %12, %13, %14, %15, %16, %17, %18, %19, %20, %21, %22, %23, %24, %25, %26, %27, %28, %29, %30, %31}, {%32, %33, %34, %35}, db, p, 1, 1, 1;\n}\n"
    : "+f"(d[0]), "+f"(d[1]), "+f"(d[2]), "+f"(d[3]), "+f"(d[4]), "+f"(d[5]), "+f"(d[6]), "+f"(d[7]), "+f"(d[8]), "+f"(d[9]), "+f"(d[10]), "+f"(d[11]), "+f"(d[12]), "+f"(d[13]), "+f"(d[14]), "+f"(d[15]), "+f"(d[16]), "+f"(d[17]), "+f"(d[18]), "+f"(d[19]), "+f"(d[20]), "+f"(d[21]), "+f"(d[22]), "+f"(d[23]), "+f"(d[24]), "+f"(d[25]), "+f"(d[26]), "+f"(d[27]), "+f"(d[28]), "+f"(d[29]), "+f"(d[30]), "+f"(d[31])
    : "r"(a0), "r"(a1), "r"(a2), "r"(a3), "r"(b), "n"(OFF), "n"(HI), "n"(SC));
}
template <int OFFA, uint32_t HIA, int OFFB, uint32_t HIB, int SC> __device__ __forceinline__ void wgmma_ss_n64_tt(float (&d)[32], uint32_t a, uint32_t b) {
  asm volatile("{\n.reg .pred p;\n.reg .b32 lo, lq;\n.reg .b64 da, db;\nsetp.ne.b32 p, %38, 0;\nadd.u32 lo, %32, %34;\nmov.b64 da, {lo, %35};\nadd.u32 lq, %33, %36;\nmov.b64 db, {lq, %37};\n"
    "wgmma.mma_async.sync.aligned.m64n64k16.f32.bf16.bf16 {%0, %1, %2, %3, %4, %5, %6, %7, %8, %9, %10, %11, %12, %13, %14, %15, %16, %17, %18, %19, %20, %21, %22, %23, %24, %25, %26, %27, %28, %29, %30, %31}, da, db, p, 1, 1, 1, 1;\n}\n"
    : "+f"(d[0]), "+f"(d[1]), "+f"(d[2]), "+f"(d[3]), "+f"(d[4]), "+f"(d[5]), "+f"(d[6]), "+f"(d[7]), "+f"(d[8]), "+f"(d[9]), "+f"(d[10]), "+f"(d[11]), "+f"(d[12]), "+f"(d[13]), "+f"(d[14]), "+f"(d[15]), "+f"(d[16]), "+f"(d[17]), "+f"(d[18]), "+f"(d[19]), "+f"(d[20]), "+f"(d[21]), "+f"(d[22]), "+f"(d[23]), "+f"(d[24]), "+f"(d[25]), "+f"(d[26]), "+f"(d[27]), "+f"(d[28]), "+f"(d[29]), "+f"(d[30]), "+f"(d[31])
    : "r"(a), "r"(b), "n"(OFFA), "n"(HIA), "n"(OFFB), "n"(HIB), "n"(SC));
}
template <int OFFA, uint32_t HIA, int OFFB, uint32_t HIB, int SC> __device__ __forceinline__ void wgmma_ss_n64_nt(float (&d)[32], uint32_t a, uint32_t b) {
  asm volatile("{\n.reg .pred p;\n.reg .b32 lo, lq;\n.reg .b64 da, db;\nsetp.ne.b32 p, %38, 0;\nadd.u32 lo, %32, %34;\nmov.b64 da, {lo, %35};\nadd.u32 lq, %33, %36;\nmov.b64 db, {lq, %37};\n"
    "wgmma.mma_async.sync.aligned.m64n64k16.f32.bf16.bf16 {%0, %1, %2, %3, %4, %5, %6, %7, %8, %9, %10, %11, %12, %13, %14, %15, %16, %17, %18, %19, %20, %21, %22, %23, %24, %25, %26, %27, %28, %29, %30, %31}, da, db, p, 1, 1, 0, 1;\n}\n"
    : "+f"(d[0]), "+f"(d[1]), "+f"(d[2]), "+f"(d[3]), "+f"(d[4]), "+f"(d[5]), "+f"(d[6]), "+f"(d[7]), "+f"(d[8]), "+f"(d[9]), "+f"(d[10]), "+f"(d[11]), "+f"(d[12]), "+f"(d[13]), "+f"(d[14]), "+f"(d[15]), "+f"(d[16]), "+f"(d[17]), "+f"(d[18]), "+f"(d[19]), "+f"(d[20]), "+f"(d[21]), "+f"(d[22]), "+f"(d[23]), "+f"(d[24]), "+f"(d[25]), "+f"(d[26]), "+f"(d[27]), "+f"(d[28]), "+f"(d[29]), "+f"(d[30]), "+f"(d[31])
    : "r"(a), "r"(b), "n"(OFFA), "n"(HIA), "n"(OFFB), "n"(HIB), "n"(SC));
}
template <int OFFA, uint32_t HIA, int OFFB, uint32_t HIB, int SC> __device__ __forceinline__ void wgmma_ss_n56_nt(float (&d)[28], uint32_t a, uint32_t b) {
  asm volatile("{\n.reg .pred p;\n.reg .b32 lo, lq;\n.reg .b64 da, db;\nsetp.ne.b32 p, %34, 0;\nadd.u32 lo, %28, %30;\nmov.b64 da, {lo, %31};\nadd.u32 lq, %29, %32;\nmov.b64 db, {lq, %33};\n"
    "wgmma.mma_async.sync.aligned.m64n56k16.f32.bf16.bf16 {%0, %1, %2, %3, %4, %5, %6, %7, %8, %9, %10, %11, %12, %13, %14, %15, %16, %17, %18, %19, %20, %21, %22, %23, %24, %25, %26, %27}, da, db, p, 1, 1, 0, 1;\n}\n"
    : "+f"(d[0]), "+f"(d[1]), "+f"(d[2]), "+f"(d[3]), "+f"(d[4]), "+f"(d[5]), "+f"(d[6]), "+f"(d[7]), "+f"(d[8]), "+f"(d[9]), "+f"(d[10]), "+f"(d[11]), "+f"(d[12]), "+f"(d[13]), "+f"(d[14]), "+f"(d[15]), "+f"(d[16]), "+f"(d[17]), "+f"(d[18]), "+f"(d[19]), "+f"(d[20]), "+f"(d[21]), "+f"(d[22]), "+f"(d[23]), "+f"(d[24]), "+f"(d[25]), "+f"(d[26]), "+f"(d[27])
    : "r"(a), "r"(b), "n"(OFFA), "n"(HIA), "n"(OFFB), "n"(HIB), "n"(SC));
}

#define DEVINL __device__ __forceinline__

constexpr int SLOT = 28672;
constexpr int XR = 114688;
constexpr int XR2 = XR + 57344;
constexpr int PK_OFF = XR;
constexpr int V_OFF = XR + 16384;
constexpr int KV_OFF = XR + 32768;
constexpr int BARS = 229376;
constexpr int SMEM_BYTES = BARS + 512;
constexpr int B_FULL = 0, B_EMPTY = 4, B_XB = 8  , B_HB = 12  , B_XF = 16, B_EB = 17, B_KVB = 18,
              B_OF = 19  , B_OB = 21  , B_FB = 23  , B_PB = 32  ;
constexpr int EPOCH_OFF = BARS + 384;

__device__ float g_kv[2][8][56 * 32];
__device__ uint4 g_o[16][2][3584];
__device__ uint4 g_part[16][8][3][2][448];
__device__ unsigned g_cnt_kv[8 * 32];
__device__ unsigned g_cnt_o[16 * 2 * 32];
__device__ unsigned g_cnt_part[16 * 8 * 6 * 8];
#define PROF_T(idx)
#define PROF_H(idx)

DEVINL uint32_t smem_u32(const void* p) { return (uint32_t)__cvta_generic_to_shared(p); }
DEVINL unsigned clock32() { unsigned c; asm volatile("mov.u32 %0, %%clock;" : "=r"(c)); return c; }
DEVINL void mbar_init(uint32_t bar, uint32_t cnt) { asm volatile("mbarrier.init.shared::cta.b64 [%0], %1;" :: "r"(bar), "r"(cnt) : "memory"); }
DEVINL void mbar_expect_tx(uint32_t bar, uint32_t bytes) { asm volatile("mbarrier.arrive.expect_tx.shared::cta.b64 _, [%0], %1;" :: "r"(bar), "r"(bytes) : "memory"); }
DEVINL void mbar_arrive(uint32_t bar) { asm volatile("mbarrier.arrive.shared::cta.b64 _, [%0];" :: "r"(bar) : "memory"); }
DEVINL uint32_t mapa(uint32_t addr, uint32_t cta) { uint32_t r; asm("mapa.shared::cluster.u32 %0, %1, %2;" : "=r"(r) : "r"(addr), "r"(cta)); return r; }
DEVINL void mbar_arrive_remote(uint32_t raddr) { asm volatile("mbarrier.arrive.shared::cluster.b64 _, [%0];" :: "r"(raddr) : "memory"); }
DEVINL bool mbar_try_wait(uint32_t bar, uint32_t parity) {
  uint32_t ok;
  asm volatile("{\n.reg .pred p;\nmbarrier.try_wait.parity.shared::cta.b64 p, [%1], %2;\nselp.u32 %0, 1, 0, p;\n}" : "=r"(ok) : "r"(bar), "r"(parity) : "memory");
  return ok;
}
DEVINL bool mbar_try_wait_cl(uint32_t bar, uint32_t parity) {
  uint32_t ok;
  asm volatile("{\n.reg .pred p;\nmbarrier.try_wait.parity.acquire.cluster.shared::cta.b64 p, [%1], %2;\nselp.u32 %0, 1, 0, p;\n}" : "=r"(ok) : "r"(bar), "r"(parity) : "memory");
  return ok;
}
constexpr unsigned TIMEOUT = 1u << 30;
DEVINL void mbar_wait(uint32_t bar, uint32_t parity) {
  if (!mbar_try_wait(bar, parity)) {
    unsigned t0 = clock32();
    while (!mbar_try_wait(bar, parity)) { if (clock32() - t0 > TIMEOUT) break; }
  }
}
DEVINL void mbar_wait_cl(uint32_t bar, uint32_t parity) {
  if (!mbar_try_wait_cl(bar, parity)) {
    unsigned t0 = clock32();
    while (!mbar_try_wait_cl(bar, parity)) { if (clock32() - t0 > TIMEOUT) break; }
  }
}
DEVINL unsigned ld_acquire(const unsigned* p) { unsigned v; asm volatile("ld.acquire.gpu.global.u32 %0, [%1];" : "=r"(v) : "l"(p) : "memory"); return v; }
DEVINL void poll_flag(const unsigned* p, unsigned target) {
  unsigned t0 = clock32();
  while ((int)(ld_acquire(p) - target) < 0) { if (clock32() - t0 > TIMEOUT) break; __nanosleep(20); }
}
DEVINL void flag_add(unsigned* p, unsigned v) {
  asm volatile("fence.acq_rel.gpu;\nred.relaxed.gpu.global.add.u32 [%0], %1;" :: "l"(p), "r"(v) : "memory");
}
DEVINL void tma_2d(uint32_t dst, const CUtensorMap* tm, int c0, int c1, uint32_t bar) {
  asm volatile("cp.async.bulk.tensor.2d.shared::cluster.global.mbarrier::complete_tx::bytes [%0], [%1, {%3, %4}], [%2];"
    :: "r"(dst), "l"(tm), "r"(bar), "r"(c0), "r"(c1) : "memory");
}
DEVINL void bulk_load(uint32_t dst, const void* src, uint32_t bytes, uint32_t bar) {
  asm volatile("cp.async.bulk.shared::cluster.global.mbarrier::complete_tx::bytes [%0], [%1], %2, [%3];"
    :: "r"(dst), "l"(src), "r"(bytes), "r"(bar) : "memory");
}
DEVINL void wg_fence() { asm volatile("wgmma.fence.sync.aligned;" ::: "memory"); }
DEVINL void wg_commit() { asm volatile("wgmma.commit_group.sync.aligned;" ::: "memory"); }
template <int N> DEVINL void wg_wait() { asm volatile("wgmma.wait_group.sync.aligned %0;" :: "n"(N) : "memory"); }
__host__ __device__ constexpr int desc_lo(int off, int lbo) { return (off >> 4) | ((lbo >> 4) << 16); }
__host__ __device__ constexpr uint32_t desc_hi(int sbo, uint32_t swz) { return (uint32_t)(sbo >> 4) | (swz << 30); }
constexpr uint32_t HI128 = desc_hi(1024, 1), HI64 = desc_hi(512, 2), HI_O = desc_hi(7168, 0);
template <int I, int N, class F> DEVINL void static_for(F&& f) { if constexpr (I < N) { f(std::integral_constant<int, I>{}); static_for<I + 1, N>(f); } }
DEVINL void bar_sync(int id, int n) { asm volatile("bar.sync %0, %1;" :: "r"(id), "r"(n) : "memory"); }
DEVINL void bar_arrive(int id, int n) { asm volatile("bar.arrive %0, %1;" :: "r"(id), "r"(n) : "memory"); }
DEVINL void fence_async() { asm volatile("fence.proxy.async.shared::cta;" ::: "memory"); }
DEVINL uint32_t pack_bf16(float lo, float hi) { uint32_t r; asm("cvt.rn.bf16x2.f32 %0, %1, %2;" : "=r"(r) : "f"(hi), "f"(lo)); return r; }
DEVINL float bf_lo(uint32_t v) { return __uint_as_float(v << 16); }
DEVINL float bf_hi(uint32_t v) { return __uint_as_float(v & 0xffff0000u); }
DEVINL float round_bf16(float x) { return bf_lo(pack_bf16(x, 0.f) & 0xffffu); }
DEVINL float ex2(float x) { float e; asm("ex2.approx.ftz.f32 %0, %1;" : "=f"(e) : "f"(x)); return e; }
DEVINL float rcp(float x) { float r; asm("rcp.approx.ftz.f32 %0, %1;" : "=f"(r) : "f"(x)); return r; }
template <int N> DEVINL void fence_regs(float (&d)[N]) {
  #pragma unroll
  for (int i = 0; i < N; i++) asm volatile("" : "+f"(d[i]) :: "memory");
}
DEVINL void ldsm4(uint32_t addr, uint32_t& a0, uint32_t& a1, uint32_t& a2, uint32_t& a3) {
  asm volatile("ldmatrix.sync.aligned.m8n8.x4.shared.b16 {%0, %1, %2, %3}, [%4];" : "=r"(a0), "=r"(a1), "=r"(a2), "=r"(a3) : "r"(addr) : "memory");
}
DEVINL void stsm4(uint32_t addr, uint32_t a0, uint32_t a1, uint32_t a2, uint32_t a3) {
  asm volatile("stmatrix.sync.aligned.m8n8.x4.shared.b16 [%0], {%1, %2, %3, %4};" :: "r"(addr), "r"(a0), "r"(a1), "r"(a2), "r"(a3) : "memory");
}
DEVINL void mma_ones(float (&c)[4], uint32_t a0, uint32_t a1, uint32_t a2, uint32_t a3) {
  asm volatile("mma.sync.aligned.m16n8k16.row.col.f32.bf16.bf16.f32 {%0, %1, %2, %3}, {%4, %5, %6, %7}, {%8, %8}, {%0, %1, %2, %3};"
    : "+f"(c[0]), "+f"(c[1]), "+f"(c[2]), "+f"(c[3]) : "r"(a0), "r"(a1), "r"(a2), "r"(a3), "r"(0x3F803F80u));
}
DEVINL uint32_t sub_bf16x2(uint32_t a, uint32_t b) { uint32_t r; asm("sub.rn.bf16x2 %0, %1, %2;" : "=r"(r) : "r"(a), "r"(b)); return r; }
DEVINL void st_async4(uint32_t raddr, uint32_t a0, uint32_t a1, uint32_t a2, uint32_t a3, uint32_t rbar) {
  asm volatile("st.async.weak.shared::cluster.mbarrier::complete_tx::bytes.v4.b32 [%0], {%1, %2, %3, %4}, [%5];"
    :: "r"(raddr), "r"(a0), "r"(a1), "r"(a2), "r"(a3), "r"(rbar) : "memory");
}
constexpr float LOG2E = 1.4426950408889634f;

DEVINL float phi(float a, float r, float rl) { float e = ex2(a * rl) + 1e-6f; float l = fmaf(a, r, 1.000001f); return a > 0.f ? l : e; }

struct Ctx { uint32_t base, b16; int wg; int lane; };

template <int B> DEVINL void batch_begin(const Ctx& c) {
  mbar_wait(c.base + BARS + 8 * (B_FULL + ((2 * B) & 3)), (B >> 1) & 1);
  bar_sync(1 + c.wg, 256);
  wg_fence();
}
template <int B> DEVINL void batch_mid(const Ctx& c) {
  wg_commit();
  mbar_wait(c.base + BARS + 8 * (B_FULL + ((2 * B + 1) & 3)), (B >> 1) & 1);
  wg_fence();
}
template <int B> DEVINL void batch_end(const Ctx& c) {
  wg_commit();
  if (B < 14 || c.wg == 0) bar_arrive(1 + (c.wg ^ 1), 256);
}
template <int B> DEVINL void batch_release(const Ctx& c) {
  wg_wait<1>();
  if (B < 13 && c.lane == 0) mbar_arrive(c.base + BARS + 8 * (B_EMPTY + ((2 * B) & 3)));
  wg_wait<0>();
  if (B < 13 && c.lane == 0) mbar_arrive(c.base + BARS + 8 * (B_EMPTY + ((2 * B + 1) & 3)));
}
template <int B, int HALF, int AO, int NA> DEVINL void rs56_half(const Ctx& c, float (&acc)[28], const uint32_t (&a)[NA]) {
  static_for<0, 14>([&](auto K) { constexpr int k = decltype(K)::value;
    wgmma_rs_n56<desc_lo(((2 * B + HALF) & 3) * SLOT + k * 2048, 0), HI128, (HALF | k) ? 1 : 0>(acc, a[AO + 4 * k], a[AO + 4 * k + 1], a[AO + 4 * k + 2], a[AO + 4 * k + 3], c.b16); });
}
template <int B, int HALF> DEVINL void rs64_half(const Ctx& c, float (&acc)[32], const uint32_t (&a)[112]) {
  static_for<0, 14>([&](auto K) { constexpr int k = decltype(K)::value;
    wgmma_rs_n64<desc_lo(((2 * B + HALF) & 3) * SLOT + k * 1024, 14336), HI64, (HALF | k) ? 1 : 0>(acc, a[56 * HALF + 4 * k], a[56 * HALF + 4 * k + 1], a[56 * HALF + 4 * k + 2], a[56 * HALF + 4 * k + 3], c.b16); });
}

template <int C> DEVINL void g1_epilogue(const float (&acc)[32], uint32_t (&h)[56], float nl0, float nl1, float rr0, float rr1,
                                         uint32_t hdst, uint32_t hbar) {
  #pragma unroll
  for (int i = 0; i < 8; i++) {
    const float nl = (i & 1) ? nl1 : nl0, rr = (i & 1) ? rr1 : rr0;
    float g0 = acc[2 * i], g1 = acc[2 * i + 1], u0 = acc[16 + 2 * i], u1 = acc[17 + 2 * i];
    float s0 = rcp(1.f + ex2(g0 * nl)), s1 = rcp(1.f + ex2(g1 * nl));
    h[8 * C + i] = pack_bf16((g0 * u0) * (rr * s0), (g1 * u1) * (rr * s1));
  }
  st_async4(hdst + (2 * C) * 2048, h[8 * C], h[8 * C + 1], h[8 * C + 2], h[8 * C + 3], hbar + (C == 6 ? 8 : 0));
  st_async4(hdst + (2 * C + 1) * 2048, h[8 * C + 4], h[8 * C + 5], h[8 * C + 6], h[8 * C + 7], hbar + (C == 6 ? 8 : 0));
}

__global__ void __launch_bounds__(384, 1)
fused_kernel(const __grid_constant__ CUtensorMap tm_x, const __grid_constant__ CUtensorMap tm_qkv, const __grid_constant__ CUtensorMap tm_wo,
             const __grid_constant__ CUtensorMap tm_w1, const __grid_constant__ CUtensorMap tm_w3, const __grid_constant__ CUtensorMap tm_w2,
             const uint32_t* __restrict__ xg, uint32_t* __restrict__ out) {
  extern __shared__ __align__(1024) uint8_t smem_raw[];
  const uint32_t base = smem_u32(smem_raw);
  const uint32_t bars = base + BARS;
  const int warp = __shfl_sync(0xffffffff, threadIdx.x >> 5, 0), lane = threadIdx.x & 31;
  const int n = blockIdx.x & 1, p = (blockIdx.x >> 1) & 3, r = blockIdx.x >> 3, j = 2 * p + n;

  if (threadIdx.x == 256) {
    PROF_H(0);
    for (int i = 0; i < 4; i++) { mbar_init(bars + 8 * (B_FULL + i), 1); mbar_init(bars + 8 * (B_EMPTY + i), 8); mbar_init(bars + 8 * (B_XB + i), 1); mbar_init(bars + 8 * (B_HB + i), 1); }
    mbar_init(bars + 8 * B_XF, 4); mbar_init(bars + 8 * B_EB, 1); mbar_init(bars + 8 * B_KVB, 2);
    for (int i = 0; i < 2; i++) { mbar_init(bars + 8 * (B_OF + i), 8); mbar_init(bars + 8 * (B_OB + i), 1); }
    for (int i = 0; i < 9; i++) mbar_init(bars + 8 * (B_FB + i), i == 0 ? 8 : 4);
    for (int i = 0; i < 6; i++) mbar_init(bars + 8 * (B_PB + i), 1);
    asm volatile("fence.mbarrier_init.release.cluster;" ::: "memory");
    asm volatile("fence.proxy.async;" ::: "memory");
    mbar_expect_tx(bars + 8 * (B_XB + 0), 32768); mbar_expect_tx(bars + 8 * (B_XB + 1), 24576);
    for (int ch = 0; ch < 7; ch++) tma_2d(base + XR + ch * 8192, &tm_x, ch * 64, r * 128, bars + 8 * (B_XB + (ch >= 4)));
    for (int hf = 0; hf < 2; hf++) { mbar_expect_tx(bars + 8 * (B_FULL + hf), SLOT); tma_2d(base + hf * SLOT, &tm_qkv, 448 + 56 * j, 224 * hf, bars + 8 * (B_FULL + hf)); }
    mbar_expect_tx(bars + 8 * (B_XB + 2), 32768); mbar_expect_tx(bars + 8 * (B_XB + 3), 24576);
    for (int ch = 0; ch < 7; ch++) tma_2d(base + XR2 + ch * 8192, &tm_x, ch * 64, r * 128 + 64, bars + 8 * (B_XB + 2 + (ch >= 4)));
    for (int hf = 0; hf < 2; hf++) { mbar_expect_tx(bars + 8 * (B_FULL + 2 + hf), SLOT); tma_2d(base + (2 + hf) * SLOT, &tm_qkv, 896 + 56 * j, 224 * hf, bars + 8 * (B_FULL + 2 + hf)); }
    for (int i = 0; i < 2; i++) { mbar_expect_tx(bars + 8 * (B_HB + 2 * i), 24576); mbar_expect_tx(bars + 8 * (B_HB + 2 * i + 1), 4096); }
    PROF_H(1);
  } else if (threadIdx.x >= 288 && threadIdx.x < 292) {
    const CUtensorMap* t = threadIdx.x == 288 ? &tm_w1 : threadIdx.x == 289 ? &tm_w3 : threadIdx.x == 290 ? &tm_w2 : &tm_wo;
    asm volatile("prefetch.tensormap [%0];" :: "l"(t) : "memory");
  }
  __syncthreads();
  asm volatile("barrier.cluster.arrive.release.aligned;" ::: "memory");

  if (warp >= 8) {
    asm volatile("setmaxnreg.dec.sync.aligned.u32 40;");
    asm volatile("barrier.cluster.wait.acquire.aligned;" ::: "memory");
    if (warp == 8) {
      if (lane == 0) {
        for (int t = 4; t < 30; t++) {
          const int b = t >> 1, hf = t & 1, slot = t & 3;
          const uint32_t dst = base + slot * SLOT, fb = bars + 8 * (B_FULL + slot);
          mbar_wait(bars + 8 * (B_EMPTY + slot), ((t >> 2) & 1) ^ 1);
          mbar_expect_tx(fb, SLOT);
          if (b == 5) tma_2d(dst, &tm_qkv, 56 * j, 224 * hf, fb);
          else if (b < 10) {
            const int c = b < 5 ? b - 2 : b - 3;
            tma_2d(dst, &tm_w1, 224 * j + 32 * c, 224 * hf, fb);
            tma_2d(dst + 14336, &tm_w3, 224 * j + 32 * c, 224 * hf, fb);
          } else if (b < 14) tma_2d(dst, &tm_w2, 224 * n + 56 * ((p + 1 + b - 10) & 3), 224 * (j ^ hf), fb);
          else tma_2d(dst, &tm_wo, 224 * n + 56 * p, 224 * hf, fb);
          PROF_H(2 + t);
        }
      }
    } else if (warp == 11) {
      if (lane == 0) {
        mbar_wait(bars + 8 * (B_FB + 0), 0);
        flag_add(&g_cnt_kv[j * 32], 8);
        PROF_H(40);
        for (int w = 0; w < 2; w++) { mbar_wait(bars + 8 * (B_FB + 1 + w), 0); flag_add(&g_cnt_o[(r * 2 + w) * 32], 16); PROF_H(41 + w); }
        for (int i = 0; i < 6; i++) {
          mbar_wait(bars + 8 * (B_FB + 3 + i), 0);
          const int owner = 2 * ((p + 1 + (i >> 1)) & 3) + n;
          flag_add(&g_cnt_part[((r * 8 + owner) * 6 + i) * 8], 128);
          PROF_H(43 + i);
        }
      }
    } else {
      unsigned epoch;
      if (warp == 9) {
        asm volatile("ld.relaxed.gpu.global.u32 %0, [%1];" : "=r"(epoch) : "l"(&g_cnt_kv[j * 32]) : "memory");
        epoch &= ~127u;
        if (lane == 0) {
          asm volatile("st.shared.u32 [%0], %1;" :: "r"(base + EPOCH_OFF), "r"(epoch) : "memory");
          mbar_arrive(bars + 8 * B_EB);
        }
        if (lane < 28) reinterpret_cast<float4*>(&g_kv[((epoch >> 7) & 1) ^ 1][j][0])[r * 28 + lane] = make_float4(0.f, 0.f, 0.f, 0.f);
      } else {
        mbar_wait(bars + 8 * B_EB, 0);
        asm volatile("ld.shared.u32 %0, [%1];" : "=r"(epoch) : "r"(base + EPOCH_OFF) : "memory");
      }
      const unsigned target = epoch + 128;
      const int wsel = warp - 9;
      mbar_wait(bars + 8 * (B_FB + 0), 0);
      #pragma unroll
      for (int it = 0; it < 8; it++) {
        const uint32_t a = base + KV_OFF + (it * 8 + wsel * 4) * 128 + lane * 16;
        asm volatile("st.shared.v4.u32 [%0], {%1, %1, %1, %1};" :: "r"(a), "r"(0) : "memory");
      }
      if (lane == 0) poll_flag(&g_cnt_kv[j * 32], target);
      __syncwarp();
      {
        const float4* src = reinterpret_cast<const float4*>(&g_kv[(epoch >> 7) & 1][j][0]) + wsel * 32 + lane;
        float4 v[7];
        #pragma unroll
        for (int it = 0; it < 7; it++) asm volatile("ld.global.cg.v4.f32 {%0, %1, %2, %3}, [%4];" : "=f"(v[it].x), "=f"(v[it].y), "=f"(v[it].z), "=f"(v[it].w) : "l"(src + it * 64) : "memory");
        const int gq = lane & 7;
        #pragma unroll
        for (int it = 0; it < 7; it++) {
          const int d = it * 8 + wsel * 4 + (lane >> 3);
          const int col = gq < 7 ? (d >= 28 ? 28 : 0) + 4 * gq : 56;
          const uint32_t a = base + KV_OFF + d * 128 + (((col >> 3) ^ (d & 7)) << 4) + ((col >> 2) & 1) * 8;
          asm volatile("st.shared.v2.u32 [%0], {%1, %2};" :: "r"(a), "r"(pack_bf16(v[it].x, v[it].y)), "r"(pack_bf16(v[it].z, v[it].w)) : "memory");
        }
      }
      fence_async();
      __syncwarp();
      if (lane == 0) {
        mbar_arrive(bars + 8 * B_KVB);
        if (warp == 9) {
          PROF_H(50);
          for (int i = 0; i < 6; i++) { poll_flag(&g_cnt_part[((r * 8 + j) * 6 + i) * 8], target); mbar_arrive(bars + 8 * (B_PB + i)); PROF_H(51 + i); }
        } else {
          for (int w = 0; w < 2; w++) {
            mbar_wait(bars + 8 * (B_OF + w), 0);
            poll_flag(&g_cnt_o[(r * 2 + w) * 32], target);
            asm volatile("fence.proxy.async;" ::: "memory");
            PROF_H(57 + w);
            mbar_expect_tx(bars + 8 * (B_OB + w), 57344);
            for (int q = 0; q < 4; q++) {
              bulk_load(base + XR + w * 57344 + q * 14336, &g_o[r][w][q * 896], 14336, bars + 8 * (B_OB + w));
              __nanosleep(200);
            }
          }
        }
      }
    }
  } else {
    asm volatile("setmaxnreg.inc.sync.aligned.u32 232;");
    const int wg = warp >> 2, w = warp & 3, tid = threadIdx.x & 127;
    const int g = lane >> 2, t = lane & 3;
    Ctx c; c.base = base; c.b16 = (base & 0x3FFFF) >> 4; c.wg = wg; c.lane = lane;
    if (wg == 1) bar_arrive(1, 256);
    uint32_t a[112];
    const uint32_t frag_off = (16 * w + (lane & 7) + ((lane >> 3) & 1) * 8) * 128 + (((lane >> 4) ^ (lane & 7)) << 4);
    float m0, m1;
    {
      float s[4][4];
      #pragma unroll
      for (int q = 0; q < 4; q++) { s[q][0] = s[q][1] = s[q][2] = s[q][3] = 0.f; }
      const uint32_t xb = base + XR + wg * 57344;
      PROF_T(0);
      #pragma unroll
      for (int ch = 0; ch < 7; ch++) {
        if (ch == 0) mbar_wait(bars + 8 * (B_XB + 2 * wg), 0);
        if (ch == 4) mbar_wait(bars + 8 * (B_XB + 2 * wg + 1), 0);
        #pragma unroll
        for (int q = 0; q < 4; q++) {
          const int k = 4 * ch + q;
          ldsm4(xb + ch * 8192 + (frag_off ^ (q * 32)), a[4 * k], a[4 * k + 1], a[4 * k + 2], a[4 * k + 3]);
          mma_ones(s[q], a[4 * k], a[4 * k + 1], a[4 * k + 2], a[4 * k + 3]);
        }
      }
      m0 = ((s[0][0] + s[1][0]) + (s[2][0] + s[3][0])) * (1.f / 448.f);
      m1 = ((s[0][2] + s[1][2]) + (s[2][2] + s[3][2])) * (1.f / 448.f);
    }
    {
      const uint32_t mb0 = pack_bf16(m0, m0), mb1 = pack_bf16(m1, m1);
      #pragma unroll
      for (int i = 0; i < 112; i++) a[i] = sub_bf16x2(a[i], (i & 1) ? mb1 : mb0);
      m0 -= bf_hi(mb0); m1 -= bf_hi(mb1);
    }
    PROF_T(1);
    asm volatile("barrier.cluster.wait.acquire.aligned;" ::: "memory");
    if (wg == 1 && lane == 0) mbar_arrive_remote(mapa(bars + 8 * B_XF, n ^ 1));
    float r0, r1;
    const uint32_t tile_off = wg * 8192 + frag_off;
    {
      float acc[28];
      batch_begin<0>(c); PROF_T(2);
      rs56_half<0, 0, 0>(c, acc, a); batch_mid<0>(c); rs56_half<0, 1, 56>(c, acc, a); batch_end<0>(c);
      {
        float q0 = 0.f, q1 = 0.f, q2 = 0.f, q3 = 0.f;
        #pragma unroll
        for (int i = 0; i < 112; i += 2) {
          float l0 = bf_lo(a[i]), h0 = bf_hi(a[i]), l1 = bf_lo(a[i + 1]), h1 = bf_hi(a[i + 1]);
          q0 = fmaf(l0, l0, q0); q1 = fmaf(h0, h0, q1); q2 = fmaf(l1, l1, q2); q3 = fmaf(h1, h1, q3);
        }
        q0 += q1; q2 += q3;
        q0 += __shfl_xor_sync(0xffffffff, q0, 1); q2 += __shfl_xor_sync(0xffffffff, q2, 1);
        q0 += __shfl_xor_sync(0xffffffff, q0, 2); q2 += __shfl_xor_sync(0xffffffff, q2, 2);
        float v0 = fmaxf(q0 * (1.f / 448.f) - m0 * m0, 0.f), v1 = fmaxf(q2 * (1.f / 448.f) - m1 * m1, 0.f);
        r0 = 1.f / round_bf16(sqrtf(round_bf16(round_bf16(v0) + 1e-5f)));
        r1 = 1.f / round_bf16(sqrtf(round_bf16(round_bf16(v1) + 1e-5f)));
      }
      batch_release<0>(c); fence_regs(acc); PROF_T(3);
      const float rl0 = r0 * LOG2E, rl1 = r1 * LOG2E;
      uint32_t pk[16];
      #pragma unroll
      for (int i = 0; i < 7; i++) {
        pk[2 * i] = pack_bf16(phi(acc[4 * i], r0, rl0), phi(acc[4 * i + 1], r0, rl0));
        pk[2 * i + 1] = pack_bf16(phi(acc[4 * i + 2], r1, rl1), phi(acc[4 * i + 3], r1, rl1));
      }
      pk[14] = pk[15] = 0;
      #pragma unroll
      for (int q = 0; q < 4; q++) stsm4(base + PK_OFF + (tile_off ^ (q * 32)), pk[4 * q], pk[4 * q + 1], pk[4 * q + 2], pk[4 * q + 3]);
    }
    {
      float acc[28];
      batch_begin<1>(c); PROF_T(4);
      rs56_half<1, 0, 0>(c, acc, a); batch_mid<1>(c); rs56_half<1, 1, 56>(c, acc, a); batch_end<1>(c);
      batch_release<1>(c); fence_regs(acc); PROF_T(5);
      uint32_t pv[16];
      #pragma unroll
      for (int i = 0; i < 7; i++) {
        pv[2 * i] = pack_bf16(acc[4 * i] * r0, acc[4 * i + 1] * r0);
        pv[2 * i + 1] = pack_bf16(acc[4 * i + 2] * r1, acc[4 * i + 3] * r1);
      }
      pv[14] = pv[15] = t == 0 ? 0x3F80u : 0u;
      #pragma unroll
      for (int q = 0; q < 4; q++) stsm4(base + V_OFF + (tile_off ^ (q * 32)), pv[4 * q], pv[4 * q + 1], pv[4 * q + 2], pv[4 * q + 3]);
      fence_async();
    }
    uint32_t h[56];
    const float nl0 = -r0 * LOG2E, nl1 = -r1 * LOG2E, rr0 = r0 * r0, rr1 = r1 * r1;
    const uint32_t hdst = mapa(base + XR2 + wg * SLOT + tid * 16, n ^ 1);
    const uint32_t hbar = mapa(bars + 8 * (B_HB + 2 * wg), n ^ 1);
#define DBG_H(C)
    {
      float acc[32];
      batch_begin<2>(c); PROF_T(6);
      float kv[32];
      const uint32_t kb = c.b16 + wg * 512;
      static_for<0, 4>([&](auto K) { constexpr int k = decltype(K)::value;
        wgmma_ss_n64_tt<desc_lo(PK_OFF + k * 2048, 0), HI128, desc_lo(V_OFF + k * 2048, 0), HI128, k ? 1 : 0>(kv, kb, kb); });
      wg_commit();
      rs64_half<2, 0>(c, acc, a); batch_mid<2>(c); rs64_half<2, 1>(c, acc, a); batch_end<2>(c);
      wg_wait<2>(); fence_regs(kv);
      mbar_wait(bars + 8 * B_EB, 0);
      unsigned epoch; asm volatile("ld.shared.u32 %0, [%1];" : "=r"(epoch) : "r"(base + EPOCH_OFF) : "memory");
      float* gk = &g_kv[(epoch >> 7) & 1][j][0];
      #pragma unroll
      for (int hf = 0; hf < 2; hf++) {
        const int d = 16 * w + g + 8 * hf;
        const bool hd = d >= 28;
        float* row = gk + d * 32 + 2 * t - (hd ? 28 : 0);
        #pragma unroll
        for (int i = 0; i < 7; i++) {
          const bool ok = d < 56 && (i < 3 ? !hd : i > 3 ? hd : (hd == (t >= 2)));
          if (ok) asm volatile("red.relaxed.gpu.global.add.v2.f32 [%0], {%1, %2};" :: "l"(row + 8 * i), "f"(kv[4 * i + 2 * hf]), "f"(kv[4 * i + 2 * hf + 1]) : "memory");
        }
        if (d < 56 && t == 0) asm volatile("red.relaxed.gpu.global.add.f32 [%0], %1;" :: "l"(gk + d * 32 + 28 + (hd ? 1 : 0)), "f"(kv[28 + 2 * hf]) : "memory");
      }
      __syncwarp();
      if (lane == 0) mbar_arrive(bars + 8 * (B_FB + 0));
      batch_release<2>(c); fence_regs(acc); PROF_T(7);
      mbar_wait_cl(bars + 8 * B_XF, 0);
      g1_epilogue<0>(acc, h, nl0, nl1, rr0, rr1, hdst, hbar); DBG_H(0)
    }
#define G1_BATCH(B, C) { float acc[32]; batch_begin<B>(c); PROF_T(2 + 2 * B); \
      rs64_half<B, 0>(c, acc, a); batch_mid<B>(c); rs64_half<B, 1>(c, acc, a); batch_end<B>(c); \
      batch_release<B>(c); fence_regs(acc); PROF_T(3 + 2 * B); g1_epilogue<C>(acc, h, nl0, nl1, rr0, rr1, hdst, hbar); DBG_H(C) }
    G1_BATCH(3, 1)
    G1_BATCH(4, 2)
    {
      float acc[28];
      uint32_t pq[16];
      batch_begin<5>(c); PROF_T(12);
      rs56_half<5, 0, 0>(c, acc, a); batch_mid<5>(c); rs56_half<5, 1, 56>(c, acc, a); batch_end<5>(c);
      batch_release<5>(c); fence_regs(acc); PROF_T(13);
      #pragma unroll
      for (int i = 0; i < 7; i++) {
        pq[2 * i] = pack_bf16(phi(acc[4 * i], r0, -nl0), phi(acc[4 * i + 1], r0, -nl0));
        pq[2 * i + 1] = pack_bf16(phi(acc[4 * i + 2], r1, -nl1), phi(acc[4 * i + 3], r1, -nl1));
      }
      pq[14] = pq[15] = 0;
      #pragma unroll
      for (int q = 0; q < 4; q++) stsm4(base + PK_OFF + (tile_off ^ (q * 32)), pq[4 * q], pq[4 * q + 1], pq[4 * q + 2], pq[4 * q + 3]);
      fence_async();
    }
    {
      float acc[32], oa[32];
      mbar_wait(bars + 8 * B_KVB, 0);
      batch_begin<6>(c); PROF_T(14);
      static_for<0, 4>([&](auto K) { constexpr int k = decltype(K)::value;
        wgmma_ss_n64_nt<desc_lo(PK_OFF + k * 32, 0), HI128, desc_lo(KV_OFF + k * 2048, 0), HI128, k ? 1 : 0>(oa, c.b16 + wg * 512, c.b16); });
      wg_commit();
      rs64_half<6, 0>(c, acc, a); batch_mid<6>(c); rs64_half<6, 1>(c, acc, a); batch_end<6>(c);
      wg_wait<2>(); fence_regs(oa);
      if (lane == 0) mbar_arrive(bars + 8 * (B_OF + 0));
      const int src = lane & ~3;
      const float da0 = rcp(__shfl_sync(0xffffffff, oa[28], src) + 1e-6f), da1 = rcp(__shfl_sync(0xffffffff, oa[29], src) + 1e-6f);
      const float db0 = rcp(__shfl_sync(0xffffffff, oa[30], src) + 1e-6f), db1 = rcp(__shfl_sync(0xffffffff, oa[31], src) + 1e-6f);
      uint32_t* go = reinterpret_cast<uint32_t*>(&g_o[r][wg][0]) + (2 * w * 56 + 7 * j) * 32 + lane;
      #pragma unroll
      for (int i = 0; i < 7; i++) {
        const bool hd = i < 3 ? false : i > 3 ? true : t >= 2;
        const float ia = hd ? da1 : da0, ib = hd ? db1 : db0;
        go[i * 32] = pack_bf16(oa[4 * i] * ia, oa[4 * i + 1] * ia);
        go[(56 + i) * 32] = pack_bf16(oa[4 * i + 2] * ib, oa[4 * i + 3] * ib);
      }
      __syncwarp();
      if (lane == 0) mbar_arrive(bars + 8 * (B_FB + 1 + wg));
      batch_release<6>(c); fence_regs(acc); PROF_T(15);
      g1_epilogue<3>(acc, h, nl0, nl1, rr0, rr1, hdst, hbar); DBG_H(3)
    }
    G1_BATCH(7, 4)
    G1_BATCH(8, 5)
    G1_BATCH(9, 6)
    uint32_t hp[56];
    {
      const uint32_t hs = base + XR2 + wg * SLOT + tid * 16;
      mbar_wait_cl(bars + 8 * (B_HB + 2 * wg), 0);
      #pragma unroll
      for (int k = 0; k < 12; k++) asm volatile("ld.shared.v4.u32 {%0, %1, %2, %3}, [%4];" : "=r"(hp[4 * k]), "=r"(hp[4 * k + 1]), "=r"(hp[4 * k + 2]), "=r"(hp[4 * k + 3]) : "r"(hs + k * 2048) : "memory");
      mbar_wait_cl(bars + 8 * (B_HB + 2 * wg + 1), 0);
      #pragma unroll
      for (int k = 12; k < 14; k++) asm volatile("ld.shared.v4.u32 {%0, %1, %2, %3}, [%4];" : "=r"(hp[4 * k]), "=r"(hp[4 * k + 1]), "=r"(hp[4 * k + 2]), "=r"(hp[4 * k + 3]) : "r"(hs + k * 2048) : "memory");
      __syncwarp();
      if (lane == 0) mbar_arrive(bars + 8 * (B_OF + 1));
    }
#define G2_BATCH(B) { float acc[28]; batch_begin<B>(c); PROF_T(2 + 2 * B); \
      rs56_half<B, 0, 0>(c, acc, h); batch_mid<B>(c); rs56_half<B, 1, 0>(c, acc, hp); batch_end<B>(c); \
      batch_release<B>(c); fence_regs(acc); PROF_T(3 + 2 * B); \
      uint4* gp = &g_part[r][2 * ((p + 1 + B - 10) & 3) + n][B - 10][wg][0]; \
      _Pragma("unroll") for (int q = 0; q < 3; q++) gp[q * 128 + tid] = make_uint4(pack_bf16(acc[8 * q], acc[8 * q + 1]), pack_bf16(acc[8 * q + 2], acc[8 * q + 3]), pack_bf16(acc[8 * q + 4], acc[8 * q + 5]), pack_bf16(acc[8 * q + 6], acc[8 * q + 7])); \
      reinterpret_cast<uint2*>(gp + 384)[tid] = make_uint2(pack_bf16(acc[24], acc[25]), pack_bf16(acc[26], acc[27])); \
      __syncwarp(); if (lane == 0) mbar_arrive(bars + 8 * (B_FB + 3 + 2 * (B - 10) + wg)); }
    G2_BATCH(10)
    G2_BATCH(11)
    G2_BATCH(12)
    uint32_t pp[3][14], xr[14];
#define LOAD_PART(I) { mbar_wait(bars + 8 * (B_PB + 2 * I + wg), 0); const uint4* gp = &g_part[r][j][I][wg][0]; \
      _Pragma("unroll") for (int q = 0; q < 3; q++) asm volatile("ld.global.cg.v4.u32 {%0, %1, %2, %3}, [%4];" : "=r"(pp[I][4 * q]), "=r"(pp[I][4 * q + 1]), "=r"(pp[I][4 * q + 2]), "=r"(pp[I][4 * q + 3]) : "l"(gp + q * 128 + tid) : "memory"); \
      asm volatile("ld.global.cg.v2.u32 {%0, %1}, [%2];" : "=r"(pp[I][12]), "=r"(pp[I][13]) : "l"(reinterpret_cast<const uint2*>(gp + 384) + tid) : "memory"); }
    const int orow = (128 * r + 64 * wg + 16 * w + g) * 224 + 112 * n + 28 * p + t;
    #pragma unroll
    for (int i = 0; i < 7; i++) { xr[2 * i] = __ldg(xg + orow + 4 * i); xr[2 * i + 1] = __ldg(xg + orow + 8 * 224 + 4 * i); }
    LOAD_PART(0)
    LOAD_PART(1)
    float f[28];
    batch_begin<13>(c); PROF_T(28);
    rs56_half<13, 0, 0>(c, f, h); batch_mid<13>(c); rs56_half<13, 1, 0>(c, f, hp); batch_end<13>(c);
    batch_release<13>(c); fence_regs(f); PROF_T(29);
    LOAD_PART(2)
    #pragma unroll
    for (int i = 0; i < 14; i++) {
      f[2 * i] += bf_lo(pp[0][i]) + bf_lo(pp[1][i]) + bf_lo(pp[2][i]);
      f[2 * i + 1] += bf_hi(pp[0][i]) + bf_hi(pp[1][i]) + bf_hi(pp[2][i]);
    }
    #pragma unroll
    for (int i = 0; i < 28; i++) f[i] = f[i] * rcp(1.f + ex2(f[i] * -LOG2E));
    {
      float acc[28];
      mbar_wait(bars + 8 * (B_OB + wg), 0);
      batch_begin<14>(c); PROF_T(30);
      const uint32_t ab = c.b16 + wg * 3584;
      static_for<0, 14>([&](auto K) { constexpr int k = decltype(K)::value;
        wgmma_ss_n56_nt<desc_lo(XR + k * 256, 128), HI_O, desc_lo(k * 2048, 0), HI128, k ? 1 : 0>(acc, ab, c.b16); });
      batch_mid<14>(c);
      static_for<0, 14>([&](auto K) { constexpr int k = decltype(K)::value;
        wgmma_ss_n56_nt<desc_lo(XR + (14 + k) * 256, 128), HI_O, desc_lo(SLOT + k * 2048, 0), HI128, 1>(acc, ab, c.b16); });
      batch_end<14>(c);
      wg_wait<0>(); fence_regs(acc); PROF_T(31);
      #pragma unroll
      for (int i = 0; i < 7; i++) {
        out[orow + 4 * i] = pack_bf16(fmaf(acc[4 * i], f[4 * i], bf_lo(xr[2 * i])), fmaf(acc[4 * i + 1], f[4 * i + 1], bf_hi(xr[2 * i])));
        out[orow + 8 * 224 + 4 * i] = pack_bf16(fmaf(acc[4 * i + 2], f[4 * i + 2], bf_lo(xr[2 * i + 1])), fmaf(acc[4 * i + 3], f[4 * i + 3], bf_hi(xr[2 * i + 1])));
      }
      PROF_T(32);
    }
  }
}

typedef CUresult (*PFN_encodeTiled_t)(CUtensorMap*, CUtensorMapDataType, cuuint32_t, void*, const cuuint64_t*, const cuuint64_t*, const cuuint32_t*,
                                      const cuuint32_t*, CUtensorMapInterleave, CUtensorMapSwizzle, CUtensorMapL2promotion, CUtensorMapFloatOOBfill);
static void make_map(PFN_encodeTiled_t enc, CUtensorMap* m, const void* ptr, uint64_t cols, uint64_t rows, uint32_t bc, uint32_t br, CUtensorMapSwizzle sw) {
  cuuint64_t gd[2] = {cols, rows}; cuuint64_t gs[1] = {cols * 2};
  cuuint32_t bd[2] = {bc, br}; cuuint32_t es[2] = {1, 1};
  enc(m, CU_TENSOR_MAP_DATA_TYPE_BFLOAT16, 2, const_cast<void*>(ptr), gd, gs, bd, es, CU_TENSOR_MAP_INTERLEAVE_NONE, sw,
      CU_TENSOR_MAP_L2_PROMOTION_L2_128B, CU_TENSOR_MAP_FLOAT_OOB_FILL_NONE);
}

extern "C" void kernel_launch(void* const* d_in, const int* in_sizes, int n_in, void* d_out, int out_size) {
  (void)in_sizes; (void)n_in; (void)out_size;
  void* fn = nullptr; cudaDriverEntryPointQueryResult st;
  cudaGetDriverEntryPoint("cuTensorMapEncodeTiled", &fn, cudaEnableDefault, &st);
  PFN_encodeTiled_t enc = (PFN_encodeTiled_t)fn;
  CUtensorMap tx, tqkv, two, tw1, tw3, tw2;
  make_map(enc, &tx, d_in[0], 448, 2048, 64, 64, CU_TENSOR_MAP_SWIZZLE_128B);
  make_map(enc, &tqkv, d_in[1], 1344, 448, 64, 224, CU_TENSOR_MAP_SWIZZLE_128B);
  make_map(enc, &two, d_in[2], 448, 448, 64, 224, CU_TENSOR_MAP_SWIZZLE_128B);
  make_map(enc, &tw1, d_in[4], 1792, 448, 32, 224, CU_TENSOR_MAP_SWIZZLE_64B);
  make_map(enc, &tw3, d_in[5], 1792, 448, 32, 224, CU_TENSOR_MAP_SWIZZLE_64B);
  make_map(enc, &tw2, d_in[6], 448, 1792, 64, 224, CU_TENSOR_MAP_SWIZZLE_128B);
  cudaFuncSetAttribute(fused_kernel, cudaFuncAttributeMaxDynamicSharedMemorySize, SMEM_BYTES);
  cudaLaunchConfig_t cfg = {};
  cfg.gridDim = dim3(128); cfg.blockDim = dim3(384); cfg.dynamicSmemBytes = SMEM_BYTES; cfg.stream = cudaStreamPerThread;
  cudaLaunchAttribute at[1];
  at[0].id = cudaLaunchAttributeClusterDimension; at[0].val.clusterDim.x = 2; at[0].val.clusterDim.y = 1; at[0].val.clusterDim.z = 1;
  cfg.attrs = at; cfg.numAttrs = 1;
  cudaLaunchKernelEx(&cfg, fused_kernel, tx, tqkv, two, tw1, tw3, tw2, (const uint32_t*)d_in[0], (uint32_t*)d_out);
}
```

```cpp
#include <cuda_runtime.h>
#include <cuda.h>
#include <cuda_bf16.h>
#include <stdint.h>
#include <type_traits>

template <int OFF, uint32_t HI, int SC> __device__ __forceinline__ void wgmma_rs_n56(float (&d)[28], uint32_t a0, uint32_t a1, uint32_t a2, uint32_t a3, uint32_t b) {
  asm volatile("{\n.reg .pred p;\n.reg .b64 db;\nsetp.ne.b32 p, %35, 0;\nmov.b64 db, {%32, %34};\nadd.s64 db, db, %33;\n"
    "wgmma.mma_async.sync.aligned.m64n56k16.f32.bf16.bf16 {%0, %1, %2, %3, %4, %5, %6, %7, %8, %9, %10, %11, %12, %13, %14, %15, %16, %17, %18, %19, %20, %21, %22, %23, %24, %25, %26, %27}, {%28, %29, %30, %31}, db, p, 1, 1, 1;\n}\n"
    : "+f"(d[0]), "+f"(d[1]), "+f"(d[2]), "+f"(d[3]), "+f"(d[4]), "+f"(d[5]), "+f"(d[6]), "+f"(d[7]), "+f"(d[8]), "+f"(d[9]), "+f"(d[10]), "+f"(d[11]), "+f"(d[12]), "+f"(d[13]), "+f"(d[14]), "+f"(d[15]), "+f"(d[16]), "+f"(d[17]), "+f"(d[18]), "+f"(d[19]), "+f"(d[20]), "+f"(d[21]), "+f"(d[22]), "+f"(d[23]), "+f"(d[24]), "+f"(d[25]), "+f"(d[26]), "+f"(d[27])
    : "r"(a0), "r"(a1), "r"(a2), "r"(a3), "r"(b), "n"(OFF), "n"(HI), "n"(SC));
}
template <int OFF, uint32_t HI, int SC> __device__ __forceinline__ void wgmma_rs_n64(float (&d)[32], uint32_t a0, uint32_t a1, uint32_t a2, uint32_t a3, uint32_t b) {
  asm volatile("{\n.reg .pred p;\n.reg .b64 db;\nsetp.ne.b32 p, %39, 0;\nmov.b64 db, {%36, %38};\nadd.s64 db, db, %37;\n"
    "wgmma.mma_async.sync.aligned.m64n64k16.f32.bf16.bf16 {%0, %1, %2, %3, %4, %5, %6, %7, %8, %9, %10, %11, %12, %13, %14, %15, %16, %17, %18, %19, %20, %21, %22, %23, %24, %25, %26, %27, %28, %29, %30, %31}, {%32, %33, %34, %35}, db, p, 1, 1, 1;\n}\n"
    : "+f"(d[0]), "+f"(d[1]), "+f"(d[2]), "+f"(d[3]), "+f"(d[4]), "+f"(d[5]), "+f"(d[6]), "+f"(d[7]), "+f"(d[8]), "+f"(d[9]), "+f"(d[10]), "+f"(d[11]), "+f"(d[12]), "+f"(d[13]), "+f"(d[14]), "+f"(d[15]), "+f"(d[16]), "+f"(d[17]), "+f"(d[18]), "+f"(d[19]), "+f"(d[20]), "+f"(d[21]), "+f"(d[22]), "+f"(d[23]), "+f"(d[24]), "+f"(d[25]), "+f"(d[26]), "+f"(d[27]), "+f"(d[28]), "+f"(d[29]), "+f"(d[30]), "+f"(d[31])
    : "r"(a0), "r"(a1), "r"(a2), "r"(a3), "r"(b), "n"(OFF), "n"(HI), "n"(SC));
}
template <int OFFA, uint32_t HIA, int OFFB, uint32_t HIB, int SC> __device__ __forceinline__ void wgmma_ss_n64_tt(float (&d)[32], uint32_t a, uint32_t b) {
  asm volatile("{\n.reg .pred p;\n.reg .b64 da, db;\nsetp.ne.b32 p, %38, 0;\nmov.b64 da, {%32, %35};\nadd.s64 da, da, %34;\nmov.b64 db, {%33, %37};\nadd.s64 db, db, %36;\n"
    "wgmma.mma_async.sync.aligned.m64n64k16.f32.bf16.bf16 {%0, %1, %2, %3, %4, %5, %6, %7, %8, %9, %10, %11, %12, %13, %14, %15, %16, %17, %18, %19, %20, %21, %22, %23, %24, %25, %26, %27, %28, %29, %30, %31}, da, db, p, 1, 1, 1, 1;\n}\n"
    : "+f"(d[0]), "+f"(d[1]), "+f"(d[2]), "+f"(d[3]), "+f"(d[4]), "+f"(d[5]), "+f"(d[6]), "+f"(d[7]), "+f"(d[8]), "+f"(d[9]), "+f"(d[10]), "+f"(d[11]), "+f"(d[12]), "+f"(d[13]), "+f"(d[14]), "+f"(d[15]), "+f"(d[16]), "+f"(d[17]), "+f"(d[18]), "+f"(d[19]), "+f"(d[20]), "+f"(d[21]), "+f"(d[22]), "+f"(d[23]), "+f"(d[24]), "+f"(d[25]), "+f"(d[26]), "+f"(d[27]), "+f"(d[28]), "+f"(d[29]), "+f"(d[30]), "+f"(d[31])
    : "r"(a), "r"(b), "n"(OFFA), "n"(HIA), "n"(OFFB), "n"(HIB), "n"(SC));
}
template <int OFFA, uint32_t HIA, int OFFB, uint32_t HIB, int SC> __device__ __forceinline__ void wgmma_ss_n64_nt(float (&d)[32], uint32_t a, uint32_t b) {
  asm volatile("{\n.reg .pred p;\n.reg .b64 da, db;\nsetp.ne.b32 p, %38, 0;\nmov.b64 da, {%32, %35};\nadd.s64 da, da, %34;\nmov.b64 db, {%33, %37};\nadd.s64 db, db, %36;\n"
    "wgmma.mma_async.sync.aligned.m64n64k16.f32.bf16.bf16 {%0, %1, %2, %3, %4, %5, %6, %7, %8, %9, %10, %11, %12, %13, %14, %15, %16, %17, %18, %19, %20, %21, %22, %23, %24, %25, %26, %27, %28, %29, %30, %31}, da, db, p, 1, 1, 0, 1;\n}\n"
    : "+f"(d[0]), "+f"(d[1]), "+f"(d[2]), "+f"(d[3]), "+f"(d[4]), "+f"(d[5]), "+f"(d[6]), "+f"(d[7]), "+f"(d[8]), "+f"(d[9]), "+f"(d[10]), "+f"(d[11]), "+f"(d[12]), "+f"(d[13]), "+f"(d[14]), "+f"(d[15]), "+f"(d[16]), "+f"(d[17]), "+f"(d[18]), "+f"(d[19]), "+f"(d[20]), "+f"(d[21]), "+f"(d[22]), "+f"(d[23]), "+f"(d[24]), "+f"(d[25]), "+f"(d[26]), "+f"(d[27]), "+f"(d[28]), "+f"(d[29]), "+f"(d[30]), "+f"(d[31])
    : "r"(a), "r"(b), "n"(OFFA), "n"(HIA), "n"(OFFB), "n"(HIB), "n"(SC));
}
template <int OFFA, uint32_t HIA, int OFFB, uint32_t HIB, int SC> __device__ __forceinline__ void wgmma_ss_n56_nt(float (&d)[28], uint32_t a, uint32_t b) {
  asm volatile("{\n.reg .pred p;\n.reg .b64 da, db;\nsetp.ne.b32 p, %34, 0;\nmov.b64 da, {%28, %31};\nadd.s64 da, da, %30;\nmov.b64 db, {%29, %33};\nadd.s64 db, db, %32;\n"
    "wgmma.mma_async.sync.aligned.m64n56k16.f32.bf16.bf16 {%0, %1, %2, %3, %4, %5, %6, %7, %8, %9, %10, %11, %12, %13, %14, %15, %16, %17, %18, %19, %20, %21, %22, %23, %24, %25, %26, %27}, da, db, p, 1, 1, 0, 1;\n}\n"
    : "+f"(d[0]), "+f"(d[1]), "+f"(d[2]), "+f"(d[3]), "+f"(d[4]), "+f"(d[5]), "+f"(d[6]), "+f"(d[7]), "+f"(d[8]), "+f"(d[9]), "+f"(d[10]), "+f"(d[11]), "+f"(d[12]), "+f"(d[13]), "+f"(d[14]), "+f"(d[15]), "+f"(d[16]), "+f"(d[17]), "+f"(d[18]), "+f"(d[19]), "+f"(d[20]), "+f"(d[21]), "+f"(d[22]), "+f"(d[23]), "+f"(d[24]), "+f"(d[25]), "+f"(d[26]), "+f"(d[27])
    : "r"(a), "r"(b), "n"(OFFA), "n"(HIA), "n"(OFFB), "n"(HIB), "n"(SC));
}

#define DEVINL __device__ __forceinline__

constexpr int SLOT = 28672;
constexpr int XR = 114688;
constexpr int XR2 = XR + 57344;
constexpr int PK_OFF = XR;
constexpr int V_OFF = XR + 16384;
constexpr int KV_OFF = XR + 32768;
constexpr int KVS_OFF = XR + 40960;
constexpr int BARS = 229376;
constexpr int SMEM_BYTES = BARS + 512;
constexpr int B_FULL = 0, B_EMPTY = 4, B_XB = 8  , B_HB = 16  , B_XF = 20, B_EB = 21, B_KVB = 22,
              B_OF = 23  , B_OB = 25  , B_FB = 27  , B_NUM = 31;
constexpr uint32_t SB16 = 1024 >> 4;
constexpr int EPOCH_OFF = BARS + 384;

#define MAPV 0
#define PFD 0
__constant__ unsigned char c_map[64] = {0, 4, 8, 12, 16, 20, 1, 5, 2, 6, 3, 7, 24, 28, 9, 13, 10, 14, 11, 15, 32, 36, 17, 21, 18, 22, 19, 23, 40, 44, 25, 29, 26, 30, 27, 31, 48, 33, 37, 34, 38, 35, 39, 52, 41, 45, 42, 46, 43, 47, 56, 49, 53, 50, 54, 51, 55, 60, 57, 61, 58, 62, 59, 63};
__constant__ unsigned char c_map2[64] = {0, 1, 2, 3, 4, 8, 16, 24, 32, 40, 48, 56, 5, 9, 17, 25, 33, 41, 49, 57, 6, 10, 18, 26, 34, 42, 50, 58, 7, 11, 19, 27, 35, 43, 51, 59, 12, 20, 28, 36, 44, 52, 60, 13, 21, 29, 37, 45, 53, 61, 14, 22, 30, 38, 46, 54, 62, 15, 23, 31, 39, 47, 55, 63};
__device__ float g_kv[2][8][56 * 32];
__device__ uint4 g_o[16][2][3584];
__device__ uint4 g_part[16][8][3][2][512];
__device__ unsigned g_cnt_kv[8 * 32];
__device__ unsigned g_cnt_o[16 * 2 * 32];
#define PROF_T(idx)
#define PROF_H(idx)

DEVINL uint32_t smem_u32(const void* p) { return (uint32_t)__cvta_generic_to_shared(p); }
DEVINL unsigned clock32() { unsigned c; asm volatile("mov.u32 %0, %%clock;" : "=r"(c)); return c; }
DEVINL void mbar_init(uint32_t bar, uint32_t cnt) { asm volatile("mbarrier.init.shared::cta.b64 [%0], %1;" :: "r"(bar), "r"(cnt) : "memory"); }
DEVINL void mbar_expect_tx(uint32_t bar, uint32_t bytes) { asm volatile("mbarrier.arrive.expect_tx.shared::cta.b64 _, [%0], %1;" :: "r"(bar), "r"(bytes) : "memory"); }
DEVINL void mbar_arrive(uint32_t bar) { asm volatile("mbarrier.arrive.shared::cta.b64 _, [%0];" :: "r"(bar) : "memory"); }
DEVINL uint32_t mapa(uint32_t addr, uint32_t cta) { uint32_t r; asm("mapa.shared::cluster.u32 %0, %1, %2;" : "=r"(r) : "r"(addr), "r"(cta)); return r; }
DEVINL void mbar_arrive_remote(uint32_t raddr) { asm volatile("mbarrier.arrive.shared::cluster.b64 _, [%0];" :: "r"(raddr) : "memory"); }
DEVINL bool mbar_try_wait(uint32_t bar, uint32_t parity) {
  uint32_t ok;
  asm volatile("{\n.reg .pred p;\nmbarrier.try_wait.parity.shared::cta.b64 p, [%1], %2;\nselp.u32 %0, 1, 0, p;\n}" : "=r"(ok) : "r"(bar), "r"(parity) : "memory");
  return ok;
}
DEVINL bool mbar_try_wait_cl(uint32_t bar, uint32_t parity) {
  uint32_t ok;
  asm volatile("{\n.reg .pred p;\nmbarrier.try_wait.parity.acquire.cluster.shared::cta.b64 p, [%1], %2;\nselp.u32 %0, 1, 0, p;\n}" : "=r"(ok) : "r"(bar), "r"(parity) : "memory");
  return ok;
}
constexpr unsigned TIMEOUT = 1u << 30;
DEVINL void mbar_wait(uint32_t bar, uint32_t parity, int& budget) {
  asm volatile("{\n.reg .pred p, q;\nW_%=:\nmbarrier.try_wait.parity.shared::cta.b64 p, [%1], %2;\nadd.s32 %0, %0, -1;\nsetp.gt.and.s32 q, %0, 0, !p;\n@q bra W_%=;\n}"
    : "+r"(budget) : "r"(bar), "r"(parity) : "memory");
}
DEVINL void mbar_wait_cl(uint32_t bar, uint32_t parity, int& budget) {
  asm volatile("{\n.reg .pred p, q;\nW_%=:\nmbarrier.try_wait.parity.acquire.cluster.shared::cta.b64 p, [%1], %2;\nadd.s32 %0, %0, -1;\nsetp.gt.and.s32 q, %0, 0, !p;\n@q bra W_%=;\n}"
    : "+r"(budget) : "r"(bar), "r"(parity) : "memory");
}
DEVINL unsigned ld_relaxed(const unsigned* p) { unsigned v; asm volatile("ld.relaxed.gpu.global.u32 %0, [%1];" : "=r"(v) : "l"(p) : "memory"); return v; }
DEVINL void poll_flag(const unsigned* p, unsigned target) {
  unsigned t0 = clock32();
  while ((int)(ld_relaxed(p) - target) < 0) { if (clock32() - t0 > TIMEOUT) break; __nanosleep(20); }
}
DEVINL void flag_add(unsigned* p, unsigned v) { asm volatile("red.relaxed.gpu.global.add.u32 [%0], %1;" :: "l"(p), "r"(v) : "memory"); }
DEVINL void bulk_store(void* dst, uint32_t src, uint32_t bytes) {
  asm volatile("cp.async.bulk.global.shared::cta.bulk_group [%0], [%1], %2;" :: "l"(dst), "r"(src), "r"(bytes) : "memory");
}
DEVINL void bulk_reduce_f32(void* dst, uint32_t src, uint32_t bytes) {
  asm volatile("cp.reduce.async.bulk.global.shared::cta.bulk_group.add.f32 [%0], [%1], %2;" :: "l"(dst), "r"(src), "r"(bytes) : "memory");
}
DEVINL void bulk_commit() { asm volatile("cp.async.bulk.commit_group;" ::: "memory"); }
DEVINL void bulk_wait_all() { asm volatile("cp.async.bulk.wait_group 0;" ::: "memory"); }
DEVINL void st_b128(uint4* p, uint32_t a, uint32_t b, uint32_t c, uint32_t d) {
  asm volatile("{\n.reg .b64 lo, hi;\n.reg .b128 v;\nmov.b64 lo, {%1, %2};\nmov.b64 hi, {%3, %4};\nmov.b128 v, {lo, hi};\nst.relaxed.gpu.global.b128 [%0], v;\n}"
    :: "l"(p), "r"(a), "r"(b), "r"(c), "r"(d) : "memory");
}
DEVINL void ld_b128(const uint4* p, uint32_t& a, uint32_t& b, uint32_t& c, uint32_t& d) {
  asm volatile("{\n.reg .b64 lo, hi;\n.reg .b128 v;\nld.relaxed.gpu.global.b128 v, [%4];\nmov.b128 {lo, hi}, v;\nmov.b64 {%0, %1}, lo;\nmov.b64 {%2, %3}, hi;\n}"
    : "=r"(a), "=r"(b), "=r"(c), "=r"(d) : "l"(p) : "memory");
}
DEVINL float sqrt_approx(float x) { float r; asm("sqrt.approx.ftz.f32 %0, %1;" : "=f"(r) : "f"(x)); return r; }
DEVINL void tma_2d(uint32_t dst, const CUtensorMap* tm, int c0, int c1, uint32_t bar) {
  asm volatile("cp.async.bulk.tensor.2d.shared::cluster.global.mbarrier::complete_tx::bytes [%0], [%1, {%3, %4}], [%2];"
    :: "r"(dst), "l"(tm), "r"(bar), "r"(c0), "r"(c1) : "memory");
}
DEVINL void tma_prefetch(const CUtensorMap* tm, int c0, int c1) {
  asm volatile("cp.async.bulk.prefetch.tensor.2d.L2.global [%0, {%1, %2}];" :: "l"(tm), "r"(c0), "r"(c1) : "memory");
}
DEVINL void bulk_load(uint32_t dst, const void* src, uint32_t bytes, uint32_t bar) {
  asm volatile("cp.async.bulk.shared::cluster.global.mbarrier::complete_tx::bytes [%0], [%1], %2, [%3];"
    :: "r"(dst), "l"(src), "r"(bytes), "r"(bar) : "memory");
}
DEVINL void wg_fence() { asm volatile("wgmma.fence.sync.aligned;" ::: "memory"); }
DEVINL void wg_commit() { asm volatile("wgmma.commit_group.sync.aligned;" ::: "memory"); }
template <int N> DEVINL void wg_wait() { asm volatile("wgmma.wait_group.sync.aligned %0;" :: "n"(N) : "memory"); }
__host__ __device__ constexpr int desc_lo(int off, int lbo) { return (off >> 4) | ((lbo >> 4) << 16); }
__host__ __device__ constexpr uint32_t desc_hi(int sbo, uint32_t swz) { return (uint32_t)(sbo >> 4) | (swz << 30); }
constexpr uint32_t HI128 = desc_hi(1024, 1), HI64 = desc_hi(512, 2), HI_O = desc_hi(7168, 0);
template <int I, int N, class F> DEVINL void static_for(F&& f) { if constexpr (I < N) { f(std::integral_constant<int, I>{}); static_for<I + 1, N>(f); } }
DEVINL void bar_sync(int id, int n) { asm volatile("bar.sync %0, %1;" :: "r"(id), "r"(n) : "memory"); }
DEVINL void bar_arrive(int id, int n) { asm volatile("bar.arrive %0, %1;" :: "r"(id), "r"(n) : "memory"); }
DEVINL void fence_async() { asm volatile("fence.proxy.async.shared::cta;" ::: "memory"); }
DEVINL uint32_t pack_bf16(float lo, float hi) { uint32_t r; asm("cvt.rn.bf16x2.f32 %0, %1, %2;" : "=r"(r) : "f"(hi), "f"(lo)); return r; }
DEVINL float bf_lo(uint32_t v) { return __uint_as_float(v << 16); }
DEVINL float bf_hi(uint32_t v) { return __uint_as_float(v & 0xffff0000u); }
DEVINL float round_bf16(float x) { return bf_lo(pack_bf16(x, 0.f) & 0xffffu); }
DEVINL float ex2(float x) { float e; asm("ex2.approx.ftz.f32 %0, %1;" : "=f"(e) : "f"(x)); return e; }
DEVINL float rcp(float x) { float r; asm("rcp.approx.ftz.f32 %0, %1;" : "=f"(r) : "f"(x)); return r; }
template <int N> DEVINL void fence_regs(float (&d)[N]) {
  #pragma unroll
  for (int i = 0; i < N; i++) asm volatile("" : "+f"(d[i]) :: "memory");
}
DEVINL void ldsm4(uint32_t addr, uint32_t& a0, uint32_t& a1, uint32_t& a2, uint32_t& a3) {
  asm volatile("ldmatrix.sync.aligned.m8n8.x4.shared.b16 {%0, %1, %2, %3}, [%4];" : "=r"(a0), "=r"(a1), "=r"(a2), "=r"(a3) : "r"(addr) : "memory");
}
DEVINL void stsm4(uint32_t addr, uint32_t a0, uint32_t a1, uint32_t a2, uint32_t a3) {
  asm volatile("stmatrix.sync.aligned.m8n8.x4.shared.b16 [%0], {%1, %2, %3, %4};" :: "r"(addr), "r"(a0), "r"(a1), "r"(a2), "r"(a3) : "memory");
}
DEVINL void mma_ones(float (&c)[4], uint32_t a0, uint32_t a1, uint32_t a2, uint32_t a3) {
  asm volatile("mma.sync.aligned.m16n8k16.row.col.f32.bf16.bf16.f32 {%0, %1, %2, %3}, {%4, %5, %6, %7}, {%8, %8}, {%0, %1, %2, %3};"
    : "+f"(c[0]), "+f"(c[1]), "+f"(c[2]), "+f"(c[3]) : "r"(a0), "r"(a1), "r"(a2), "r"(a3), "r"(0x3F803F80u));
}
DEVINL uint32_t sub_bf16x2(uint32_t a, uint32_t b) { uint32_t r; asm("sub.rn.bf16x2 %0, %1, %2;" : "=r"(r) : "r"(a), "r"(b)); return r; }
DEVINL void st_async4(uint32_t raddr, uint32_t a0, uint32_t a1, uint32_t a2, uint32_t a3, uint32_t rbar) {
  asm volatile("st.async.weak.shared::cluster.mbarrier::complete_tx::bytes.v4.b32 [%0], {%1, %2, %3, %4}, [%5];"
    :: "r"(raddr), "r"(a0), "r"(a1), "r"(a2), "r"(a3), "r"(rbar) : "memory");
}
constexpr float LOG2E = 1.4426950408889634f;

DEVINL float phi(float a, float r, float rl) { float e = ex2(a * rl) + 1e-6f; float l = fmaf(a, r, 1.000001f); return a > 0.f ? l : e; }

struct Ctx { uint32_t bars; int wg; int lane; int budget; };

DEVINL void batch_begin(Ctx& c, int sp, int ph) {
  mbar_wait(c.bars + 8 * (B_FULL + sp), ph, c.budget);
  bar_sync(1 + c.wg, 256);
  wg_fence();
}
DEVINL void batch_mid(Ctx& c, int sp, int ph) {
  wg_commit();
  mbar_wait(c.bars + 8 * (B_FULL + sp + 1), ph, c.budget);
  wg_fence();
}
DEVINL void batch_rel_lo(Ctx& c, int sp) {
  wg_commit();
  wg_wait<1>();
  if (c.lane == 0) mbar_arrive(c.bars + 8 * (B_EMPTY + sp));
}
DEVINL void batch_end(Ctx& c) {
  wg_commit();
  bar_arrive(1 + (c.wg ^ 1), 256);
}
DEVINL void batch_rel_hi(Ctx& c, int sp) {
  wg_wait<0>();
  if (c.lane == 0) mbar_arrive(c.bars + 8 * (B_EMPTY + sp + 1));
}
template <int HALF, int K0, int K1, int AO, int NA> DEVINL void rs56(uint32_t d, float (&acc)[28], const uint32_t (&a)[NA]) {
  static_for<K0, K1>([&](auto K) { constexpr int k = decltype(K)::value;
    wgmma_rs_n56<desc_lo(HALF * SLOT + k * 2048, 0), HI128, (HALF | k) ? 1 : 0>(acc, a[AO + 4 * k], a[AO + 4 * k + 1], a[AO + 4 * k + 2], a[AO + 4 * k + 3], d); });
}
template <int HALF, int K0, int K1> DEVINL void rs64(uint32_t d, float (&acc)[32], const uint32_t (&a)[112]) {
  static_for<K0, K1>([&](auto K) { constexpr int k = decltype(K)::value;
    wgmma_rs_n64<desc_lo(HALF * SLOT + k * 1024, 14336), HI64, (HALF | k) ? 1 : 0>(acc, a[56 * HALF + 4 * k], a[56 * HALF + 4 * k + 1], a[56 * HALF + 4 * k + 2], a[56 * HALF + 4 * k + 3], d); });
}
template <int AO1, int NA0, int NA1> DEVINL void mma56(Ctx& c, int sp, int ph, uint32_t d, float (&acc)[28], const uint32_t (&a0)[NA0], const uint32_t (&a1)[NA1]) {
  rs56<0, 0, 14, 0>(d, acc, a0); batch_mid(c, sp, ph);
  rs56<1, 0, 4, AO1>(d, acc, a1); batch_rel_lo(c, sp);
  rs56<1, 4, 14, AO1>(d, acc, a1); batch_end(c);
}
DEVINL void mma64(Ctx& c, int sp, int ph, uint32_t d, float (&acc)[32], const uint32_t (&a)[112]) {
  rs64<0, 0, 14>(d, acc, a); batch_mid(c, sp, ph);
  rs64<1, 0, 4>(d, acc, a); batch_rel_lo(c, sp);
  rs64<1, 4, 14>(d, acc, a); batch_end(c);
}

DEVINL void g1_epilogue(const float (&acc)[32], uint32_t* h, float nl0, float nl1, float rr0, float rr1, uint32_t hdst, uint32_t hbar) {
  #pragma unroll
  for (int i = 0; i < 8; i++) {
    const float nl = (i & 1) ? nl1 : nl0, rr = (i & 1) ? rr1 : rr0;
    float g0 = acc[2 * i], g1 = acc[2 * i + 1], u0 = acc[16 + 2 * i], u1 = acc[17 + 2 * i];
    float s0 = rcp(1.f + ex2(g0 * nl)), s1 = rcp(1.f + ex2(g1 * nl));
    h[i] = pack_bf16((g0 * u0) * (rr * s0), (g1 * u1) * (rr * s1));
  }
  st_async4(hdst, h[0], h[1], h[2], h[3], hbar);
  st_async4(hdst + 2048, h[4], h[5], h[6], h[7], hbar);
}

struct Maps { CUtensorMap x, qkv, wo, w1, w3, w2; };

template <bool PREFETCH> DEVINL void tile_load(const Maps& m, int t, int n, int p, uint32_t dst, uint32_t fb) {
  const int b = t >> 1, hf = t & 1, j = 2 * p + n;
  const CUtensorMap* tm;
  int c0, c1 = 224 * hf;
  if (b < 3) { tm = &m.qkv; c0 = 896 - 448 * b + 56 * j - 8 * n; }
  else if (b < 10) { tm = &m.w1; c0 = 224 * j + 32 * (b - 3); }
  else {
    const int ch = (p + 1 + b - 10 - (b == 14)) & 3;
    c0 = 224 * n + 56 * ch - 8 * (ch & 1);
    if (b < 14) { tm = &m.w2; c1 = 224 * (j ^ hf); } else tm = &m.wo;
  }
  if (PREFETCH) tma_prefetch(tm, c0, c1); else tma_2d(dst, tm, c0, c1, fb);
  if (b >= 3 && b < 10) { if (PREFETCH) tma_prefetch(&m.w3, c0, c1); else tma_2d(dst + 14336, &m.w3, c0, c1, fb); }
}

__global__ void __cluster_dims__(2, 1, 1) __launch_bounds__(384, 1)
fused_kernel(const __grid_constant__ Maps maps, const uint32_t* __restrict__ xg, uint32_t* __restrict__ out) {
  extern __shared__ __align__(1024) uint8_t smem_raw[];
  const uint32_t base = smem_u32(smem_raw);
  const uint32_t bars = base + BARS;
  const int warp = __shfl_sync(0xffffffff, threadIdx.x >> 5, 0), lane = threadIdx.x & 31;
  const int cidx = blockIdx.x >> 1;
  const int n = blockIdx.x & 1, p = cidx & 3, r = cidx >> 2, j = 2 * p + n;
  if ((base & 0x3FFFF) != SB16 * 16) return;

  if (warp == 8) {
    if (lane == 0) {
      PROF_H(0);
      #pragma unroll
      for (int i = 0; i < 8; i++) mbar_init(bars + 8 * (B_XB + i), 1);
      #pragma unroll
      for (int i = 0; i < 4; i++) mbar_init(bars + 8 * (B_FULL + i), 1);
      fence_async();
    }
    __syncwarp();
    bar_arrive(3, 384);
    asm volatile("barrier.cluster.arrive.relaxed.aligned;" ::: "memory");
    if (lane == 0) {
      PROF_H(59);
      #pragma unroll 1
      for (int ch = 0; ch < 7; ch++) {
        if (!(ch & 1)) mbar_expect_tx(bars + 8 * (B_XB + (ch >> 1)), ch == 6 ? 8192 : 16384);
        tma_2d(base + XR + ch * 8192, &maps.x, ch * 64, r * 128, bars + 8 * (B_XB + (ch >> 1)));
        PROF_H(32 + ch);
      }
      #pragma unroll 1
      for (int t = 0; t < 2; t++) { mbar_expect_tx(bars + 8 * (B_FULL + t), SLOT); tma_2d(base + t * SLOT, &maps.qkv, 896 + 56 * j - 8 * n, 224 * t, bars + 8 * (B_FULL + t)); PROF_H(53 + t); }
    }
    __syncwarp();
  } else if (warp == 10 && lane == 0) {
    #pragma unroll
    for (int i = B_EMPTY; i < B_NUM; i++) {
      if (i >= B_XB && i < B_HB) continue;
      mbar_init(bars + 8 * i, i < B_XB || i == B_OF + 1 ? 8 : i == B_XF || i >= B_FB ? 4 : i == B_KVB || i == B_OF ? 2 : 1);
    }
    #pragma unroll
    for (int i = 0; i < 4; i++) mbar_expect_tx(bars + 8 * (B_HB + i), (i & 1) ? 4096 : 24576);
    asm volatile("st.shared.u32 [%0], %1;" :: "r"(base + EPOCH_OFF + 4), "r"(0) : "memory");
    asm volatile("fence.mbarrier_init.release.cluster;" ::: "memory");
    fence_async();
  }
  __syncwarp();

  if (warp > 7) {
    asm volatile("setmaxnreg.dec.sync.aligned.u32 40;");
    int budget = 1 << 22;
    if (warp == 8) {
      bar_sync(4, 64);
      if (lane == 0) {
        #pragma unroll 1
        for (int ch = 0; ch < 7; ch++) {
          if (!(ch & 1)) mbar_expect_tx(bars + 8 * (B_XB + 4 + (ch >> 1)), ch == 6 ? 8192 : 16384);
          tma_2d(base + XR2 + ch * 8192, &maps.x, ch * 64, r * 128 + 64, bars + 8 * (B_XB + 4 + (ch >> 1)));
          PROF_H(43 + ch);
        }
        #pragma unroll 1
        for (int t = 2; t < 4; t++) { mbar_expect_tx(bars + 8 * (B_FULL + t), SLOT); tma_2d(base + t * SLOT, &maps.qkv, 448 + 56 * j - 8 * n, 224 * (t & 1), bars + 8 * (B_FULL + t)); }
        PROF_H(1);
        #pragma unroll 1
        for (int t = 4; t < 30; t++) {
          const int slot = t & 3;
          const uint32_t fb = bars + 8 * (B_FULL + slot);
          mbar_wait(bars + 8 * (B_EMPTY + slot), ((t >> 2) & 1) ^ 1, budget);
          mbar_expect_tx(fb, SLOT);
          tile_load<false>(maps, t, n, p, base + slot * SLOT, fb);
          PROF_H(2 + t);
        }
      }
      __syncwarp();
      asm volatile("barrier.cluster.wait.acquire.aligned;" ::: "memory");
    } else {
      asm volatile("barrier.cluster.arrive.relaxed.aligned;" ::: "memory");
      if (warp == 11) {
        if (lane < 4) asm volatile("prefetch.tensormap [%0];" :: "l"(&maps.wo + lane) : "memory");
        bar_sync(3, 384);
        if (lane == 0) {
          mbar_wait(bars + 8 * B_EB, 0, budget);
          unsigned epoch; asm volatile("ld.shared.u32 %0, [%1];" : "=r"(epoch) : "r"(base + EPOCH_OFF) : "memory");
          #pragma unroll 1
          for (int w = 0; w < 2; w++) {
            mbar_wait(bars + 8 * (B_FB + w), 0, budget);
            bulk_reduce_f32(&g_kv[(epoch >> 7) & 1][j][0], base + KVS_OFF + w * 8192, 7168);
            bulk_commit();
          }
          bulk_wait_all();
          flag_add(&g_cnt_kv[j * 32], 8);
          PROF_H(40);
          #pragma unroll 1
          for (int w = 0; w < 2; w++) {
            mbar_wait(bars + 8 * (B_FB + 2 + w), 0, budget);
            #pragma unroll 1
            for (int q = 0; q < 8; q++) bulk_store(&g_o[r][w][(q * 56 + 7 * j) * 8], base + V_OFF + w * 8192 + q * 896, 896);
            bulk_commit();
            bulk_wait_all();
            flag_add(&g_cnt_o[(r * 2 + w) * 32], 16);
            mbar_arrive(bars + 8 * (B_OF + 0));
            PROF_H(41 + w);
          }
        }
        __syncwarp();
        asm volatile("barrier.cluster.wait.acquire.aligned;" ::: "memory");
      } else {
        unsigned epoch;
        if (warp == 9) {
          asm volatile("ld.relaxed.gpu.global.u32 %0, [%1];" : "=r"(epoch) : "l"(&g_cnt_kv[j * 32]) : "memory");
          bar_sync(3, 384);
          epoch &= ~127u;
          if (lane == 0) {
            asm volatile("st.shared.u32 [%0], %1;" :: "r"(base + EPOCH_OFF), "r"(epoch) : "memory");
            mbar_arrive(bars + 8 * B_EB);
          }
          if (lane < 28) reinterpret_cast<float4*>(&g_kv[((epoch >> 7) & 1) ^ 1][j][0])[r * 28 + lane] = make_float4(0.f, 0.f, 0.f, 0.f);
        } else {
          bar_arrive(4, 64);
          bar_sync(3, 384);
          mbar_wait(bars + 8 * B_EB, 0, budget);
          asm volatile("ld.shared.u32 %0, [%1];" : "=r"(epoch) : "r"(base + EPOCH_OFF) : "memory");
        }
        asm volatile("barrier.cluster.wait.acquire.aligned;" ::: "memory");
        const unsigned target = epoch + 128;
        const int wsel = warp - 9;
        mbar_wait(bars + 8 * (B_FB + 0), 0, budget);
        #pragma unroll 1
        for (int it = 0; it < 8; it++) {
          const uint32_t a = base + KV_OFF + (it * 8 + wsel * 4) * 128 + lane * 16;
          asm volatile("st.shared.v4.u32 [%0], {%1, %1, %1, %1};" :: "r"(a), "r"(0) : "memory");
        }
        if (lane == 0) poll_flag(&g_cnt_kv[j * 32], target);
        __syncwarp();
        {
          const float4* src = reinterpret_cast<const float4*>(&g_kv[(epoch >> 7) & 1][j][0]) + wsel * 32 + lane;
          float4 v[7];
          #pragma unroll
          for (int it = 0; it < 7; it++) asm volatile("ld.global.cg.v4.f32 {%0, %1, %2, %3}, [%4];" : "=f"(v[it].x), "=f"(v[it].y), "=f"(v[it].z), "=f"(v[it].w) : "l"(src + it * 64) : "memory");
          const int d0 = wsel * 4 + (lane >> 3);
          const int gq = (lane ^ d0) & 7;
          #pragma unroll
          for (int it = 0; it < 7; it++) {
            const int d = it * 8 + d0;
            const int col = gq < 7 ? (d >= 28 ? 28 : 0) + 4 * gq : 56;
            const uint32_t a = base + KV_OFF + d * 128 + (((col >> 3) ^ d0) << 4) + ((col >> 2) & 1) * 8;
            asm volatile("st.shared.v2.u32 [%0], {%1, %2};" :: "r"(a), "r"(pack_bf16(v[it].x, v[it].y)), "r"(pack_bf16(v[it].z, v[it].w)) : "memory");
          }
        }
        fence_async();
        __syncwarp();
        if (lane == 0) {
          mbar_arrive(bars + 8 * B_KVB);
          if (warp == 9) {
            PROF_H(50);
          } else {
            #pragma unroll 1
            for (int w = 0; w < 2; w++) {
              mbar_wait(bars + 8 * (B_OF + w), 0, budget);
              poll_flag(&g_cnt_o[(r * 2 + w) * 32], target);
              PROF_H(57 + w);
              mbar_expect_tx(bars + 8 * (B_OB + w), 57344);
              #pragma unroll 1
              for (int q = 0; q < 4; q++) {
                bulk_load(base + XR + w * 57344 + q * 14336, &g_o[r][w][q * 896], 14336, bars + 8 * (B_OB + w));
                __nanosleep(200);
              }
            }
          }
        }
      }
    }
  } else {
    PROF_T(40);
    asm volatile("barrier.cluster.arrive.relaxed.aligned;" ::: "memory");
    asm volatile("setmaxnreg.inc.sync.aligned.u32 232;");
    const int wg = warp >> 2, w = warp & 3, tid = threadIdx.x & 127;
    const int g = lane >> 2, t = lane & 3;
    Ctx c; c.bars = bars; c.wg = wg; c.lane = lane; c.budget = 1 << 22;
    int& budget = c.budget;
    PROF_T(42);
    bar_sync(3, 384);
    PROF_T(43);
    if (wg == 1) bar_arrive(1, 256);
    uint32_t a[112];
    const uint32_t frag_off = (16 * w + (lane & 7) + ((lane >> 3) & 1) * 8) * 128 + (((lane >> 4) ^ (lane & 7)) << 4);
    float m0, m1;
    {
      float s[4][4];
      #pragma unroll
      for (int q = 0; q < 4; q++) { s[q][0] = s[q][1] = s[q][2] = s[q][3] = 0.f; }
      const uint32_t xb = base + XR + wg * 57344;
      PROF_T(0);
      #pragma unroll
      for (int q = 0; q < 4; q++) {
        mbar_wait(bars + 8 * (B_XB + 4 * wg + q), 0, budget);
        PROF_T(34 + q);
        #pragma unroll
        for (int k = 8 * q; k < 8 * q + 8 && k < 28; k++) ldsm4(xb + (k >> 2) * 8192 + (frag_off ^ ((k & 3) * 32)), a[4 * k], a[4 * k + 1], a[4 * k + 2], a[4 * k + 3]);
        #pragma unroll
        for (int k = 8 * q; k < 8 * q + 8 && k < 28; k++) mma_ones(s[k & 3], a[4 * k], a[4 * k + 1], a[4 * k + 2], a[4 * k + 3]);
      }
      m0 = ((s[0][0] + s[1][0]) + (s[2][0] + s[3][0])) * (1.f / 448.f);
      m1 = ((s[0][2] + s[1][2]) + (s[2][2] + s[3][2])) * (1.f / 448.f);
    }
    {
      const uint32_t mb0 = pack_bf16(m0, m0), mb1 = pack_bf16(m1, m1);
      #pragma unroll
      for (int i = 0; i < 112; i++) a[i] = sub_bf16x2(a[i], (i & 1) ? mb1 : mb0);
      m0 -= bf_hi(mb0); m1 -= bf_hi(mb1);
    }
    PROF_T(1);
    float r0, r1;
    const uint32_t tile_off = wg * 8192 + frag_off;
    const uint32_t sb = SB16 + blockIdx.y;
    const uint32_t dq = sb + n;
    {
      float acc[28];
      batch_begin(c, 0, 0); PROF_T(2);
      mma56<56>(c, 0, 0, dq, acc, a, a);
      PROF_T(38);
      asm volatile("barrier.cluster.wait.acquire.aligned;" ::: "memory");
      PROF_T(39);
      if (wg == 1 && lane == 0) mbar_arrive_remote(mapa(bars + 8 * B_XF, n ^ 1));
      {
        float q0, q1, q2, q3;
        asm volatile("ld.volatile.shared.f32 %0, [%1];" : "=f"(q0) : "r"(base + EPOCH_OFF + 4) : "memory");
        q1 = q2 = q3 = q0;
        #pragma unroll
        for (int i = 0; i < 112; i += 2) {
          float l0 = bf_lo(a[i]), h0 = bf_hi(a[i]), l1 = bf_lo(a[i + 1]), h1 = bf_hi(a[i + 1]);
          q0 = fmaf(l0, l0, q0); q1 = fmaf(h0, h0, q1); q2 = fmaf(l1, l1, q2); q3 = fmaf(h1, h1, q3);
        }
        q0 += q1; q2 += q3;
        q0 += __shfl_xor_sync(0xffffffff, q0, 1); q2 += __shfl_xor_sync(0xffffffff, q2, 1);
        q0 += __shfl_xor_sync(0xffffffff, q0, 2); q2 += __shfl_xor_sync(0xffffffff, q2, 2);
        float v0 = fmaxf(q0 * (1.f / 448.f) - m0 * m0, 0.f), v1 = fmaxf(q2 * (1.f / 448.f) - m1 * m1, 0.f);
        r0 = rcp(round_bf16(sqrt_approx(round_bf16(round_bf16(v0) + 1e-5f))));
        r1 = rcp(round_bf16(sqrt_approx(round_bf16(round_bf16(v1) + 1e-5f))));
      }
      batch_rel_hi(c, 0); fence_regs(acc); PROF_T(3);
      uint32_t pv[16];
      #pragma unroll
      for (int i = 0; i < 7; i++) {
        pv[2 * i] = pack_bf16(acc[4 * i] * r0, acc[4 * i + 1] * r0);
        pv[2 * i + 1] = pack_bf16(acc[4 * i + 2] * r1, acc[4 * i + 3] * r1);
      }
      pv[14] = pv[15] = t == 0 ? 0x3F80u : 0u;
      #pragma unroll
      for (int q = 0; q < 4; q++) stsm4(base + V_OFF + (tile_off ^ (q * 32)), pv[4 * q], pv[4 * q + 1], pv[4 * q + 2], pv[4 * q + 3]);
    }
    const float nl0 = -r0 * LOG2E, nl1 = -r1 * LOG2E;
#define PHI_EPILOGUE() { uint32_t pk[16]; \
      _Pragma("unroll") for (int i = 0; i < 7; i++) { \
        pk[2 * i] = pack_bf16(phi(acc[4 * i], r0, -nl0), phi(acc[4 * i + 1], r0, -nl0)); \
        pk[2 * i + 1] = pack_bf16(phi(acc[4 * i + 2], r1, -nl1), phi(acc[4 * i + 3], r1, -nl1)); } \
      pk[14] = pk[15] = 0; \
      _Pragma("unroll") for (int q = 0; q < 4; q++) stsm4(base + PK_OFF + (tile_off ^ (q * 32)), pk[4 * q], pk[4 * q + 1], pk[4 * q + 2], pk[4 * q + 3]); \
      fence_async(); }
    {
      float acc[28];
      batch_begin(c, 2, 0); PROF_T(4);
      mma56<56>(c, 2, 0, dq + 2 * (SLOT >> 4), acc, a, a);
      batch_rel_hi(c, 2); fence_regs(acc); PROF_T(5);
      PHI_EPILOGUE()
    }
    {
      float acc[28], kv[32];
      batch_begin(c, 0, 1); PROF_T(6);
      const uint32_t kb = sb + wg * 512;
      static_for<0, 4>([&](auto K) { constexpr int k = decltype(K)::value;
        wgmma_ss_n64_tt<desc_lo(PK_OFF + k * 2048, 0), HI128, desc_lo(V_OFF + k * 2048, 0), HI128, k ? 1 : 0>(kv, kb, kb); });
      mma56<56>(c, 0, 1, dq, acc, a, a);
      fence_regs(kv);
      #pragma unroll
      for (int hf = 0; hf < 2; hf++) {
        const int d = 16 * w + g + 8 * hf;
        const bool hd = d >= 28;
        const uint32_t row = base + KVS_OFF + wg * 8192 + d * 128;
        const int e2 = t - (hd ? 14 : 0);
        #pragma unroll
        for (int i = 0; i < 7; i++) {
          const bool ok = d < 56 && (i < 3 ? !hd : i > 3 ? hd : (hd == (t >= 2)));
          const int e = e2 + 4 * i;
          if (ok) asm volatile("st.shared.v2.f32 [%0], {%1, %2};" :: "r"(row + (((e >> 1) ^ g) << 4) + (e & 1) * 8), "f"(kv[4 * i + 2 * hf]), "f"(kv[4 * i + 2 * hf + 1]) : "memory");
        }
        if (d < 56 && t == 0) asm volatile("st.shared.v4.f32 [%0], {%1, %2, %3, %3};" :: "r"(row + ((7 ^ g) << 4)), "f"(hd ? 0.f : kv[28 + 2 * hf]), "f"(hd ? kv[28 + 2 * hf] : 0.f), "f"(0.f) : "memory");
      }
      fence_async();
      __syncwarp();
      if (lane == 0) mbar_arrive(bars + 8 * (B_FB + wg));
      batch_rel_hi(c, 0); fence_regs(acc); PROF_T(7);
      PHI_EPILOGUE()
    }
    uint32_t h[56];
    const float rr0 = r0 * r0, rr1 = r1 * r1;
    uint32_t hdst = mapa(base + XR2 + wg * SLOT + tid * 16, n ^ 1);
    const uint32_t hbar = mapa(bars + 8 * (B_HB + 2 * wg), n ^ 1);
    mbar_wait_cl(bars + 8 * B_XF, 0, budget);
#define DBG_H(C, H)
#define G1_LOOP(B0, HO) _Pragma("unroll 1") for (int i = 0; i < 3; i++) { \
      const int sp = 2 * ((i & 1) ^ 1), ph = i == 0; float acc[32]; \
      batch_begin(c, sp, ph); PROF_T(2 + 2 * (B0 + i)); \
      mma64(c, sp, ph, sb + sp * (SLOT >> 4), acc, a); \
      _Pragma("unroll") for (int q = 0; q < 16; q++) h[HO + q] = h[HO + 8 + q]; \
      batch_rel_hi(c, sp); fence_regs(acc); PROF_T(3 + 2 * (B0 + i)); \
      g1_epilogue(acc, h + HO + 16, nl0, nl1, rr0, rr1, hdst, hbar + (B0 == 7 && i == 2 ? 8 : 0)); hdst += 4096; DBG_H(B0 - 3 + i, h + HO + 16) }
    #pragma unroll
    for (int q = 8; q < 24; q++) h[q] = 0;
    G1_LOOP(3, 0)
    {
      float acc[32], oa[32];
      mbar_wait(bars + 8 * B_KVB, 0, budget);
      batch_begin(c, 0, 1); PROF_T(14);
      static_for<0, 4>([&](auto K) { constexpr int k = decltype(K)::value;
        wgmma_ss_n64_nt<desc_lo(PK_OFF + k * 32, 0), HI128, desc_lo(KV_OFF + k * 2048, 0), HI128, k ? 1 : 0>(oa, sb + wg * 512, sb); });
      mma64(c, 0, 1, sb, acc, a);
      fence_regs(oa);
      const int src = lane & ~3;
      const float da0 = rcp(__shfl_sync(0xffffffff, oa[28], src) + 1e-6f), da1 = rcp(__shfl_sync(0xffffffff, oa[29], src) + 1e-6f);
      const float db0 = rcp(__shfl_sync(0xffffffff, oa[30], src) + 1e-6f), db1 = rcp(__shfl_sync(0xffffffff, oa[31], src) + 1e-6f);
      const uint32_t so = base + V_OFF + wg * 8192 + w * 1792 + lane * 4;
      #pragma unroll
      for (int i = 0; i < 7; i++) {
        const bool hd = i < 3 ? false : i > 3 ? true : t >= 2;
        const float ia = hd ? da1 : da0, ib = hd ? db1 : db0;
        asm volatile("st.shared.u32 [%0], %1;" :: "r"(so + i * 128), "r"(pack_bf16(oa[4 * i] * ia, oa[4 * i + 1] * ia)) : "memory");
        asm volatile("st.shared.u32 [%0], %1;" :: "r"(so + 896 + i * 128), "r"(pack_bf16(oa[4 * i + 2] * ib, oa[4 * i + 3] * ib)) : "memory");
      }
      fence_async();
      __syncwarp();
      if (lane == 0) mbar_arrive(bars + 8 * (B_FB + 2 + wg));
      batch_rel_hi(c, 0); fence_regs(acc); PROF_T(15);
      g1_epilogue(acc, h + 24, nl0, nl1, rr0, rr1, hdst, hbar); hdst += 4096; DBG_H(3, h + 24)
    }
    #pragma unroll
    for (int q = 40; q < 56; q++) h[q] = 0;
    G1_LOOP(7, 32)
    uint32_t hp[56];
    {
      const uint32_t hs = base + XR2 + wg * SLOT + tid * 16;
      mbar_wait_cl(bars + 8 * (B_HB + 2 * wg), 0, budget);
      #pragma unroll
      for (int k = 0; k < 12; k++) asm volatile("ld.shared.v4.u32 {%0, %1, %2, %3}, [%4];" : "=r"(hp[4 * k]), "=r"(hp[4 * k + 1]), "=r"(hp[4 * k + 2]), "=r"(hp[4 * k + 3]) : "r"(hs + k * 2048) : "memory");
      mbar_wait_cl(bars + 8 * (B_HB + 2 * wg + 1), 0, budget);
      #pragma unroll
      for (int k = 12; k < 14; k++) asm volatile("ld.shared.v4.u32 {%0, %1, %2, %3}, [%4];" : "=r"(hp[4 * k]), "=r"(hp[4 * k + 1]), "=r"(hp[4 * k + 2]), "=r"(hp[4 * k + 3]) : "r"(hs + k * 2048) : "memory");
      __syncwarp();
      if (lane == 0) mbar_arrive(bars + 8 * (B_OF + 1));
    }
    float tagf;
    {
      mbar_wait(bars + 8 * B_EB, 0, budget);
      unsigned epoch; asm volatile("ld.shared.u32 %0, [%1];" : "=r"(epoch) : "r"(base + EPOCH_OFF) : "memory");
      tagf = __uint_as_float((0x4000u | ((epoch >> 7) & 0x1fffu)) << 16);
    }
    #pragma unroll 1
    for (int i = 0; i < 3; i++) {
      const int sp = 2 * (i & 1), ph = i < 2, ch = (p + 1 + i) & 3;
      float acc[28];
      batch_begin(c, sp, ph); PROF_T(22 + 2 * i);
      mma56<0>(c, sp, ph, sb + sp * (SLOT >> 4) + (ch & 1), acc, h, hp);
      uint4* gp = &g_part[r][2 * ch + n][i][wg][tid];
      batch_rel_hi(c, sp); fence_regs(acc); PROF_T(23 + 2 * i);
      #pragma unroll
      for (int q = 0; q < 4; q++) st_b128(gp + q * 128, pack_bf16(acc[7 * q], acc[7 * q + 1]), pack_bf16(acc[7 * q + 2], acc[7 * q + 3]), pack_bf16(acc[7 * q + 4], acc[7 * q + 5]), pack_bf16(acc[7 * q + 6], tagf));
    }
    uint32_t pp[3][16], xr[14];
#define LOAD_PART(I) { const uint4* gp = &g_part[r][j][I][wg][tid]; \
      _Pragma("unroll") for (int q = 0; q < 4; q++) ld_b128(gp + q * 128, pp[I][4 * q], pp[I][4 * q + 1], pp[I][4 * q + 2], pp[I][4 * q + 3]); }
#define ADD_PART(I) { const uint32_t tg = __float_as_uint(tagf); const unsigned t0 = clock32(); \
      while (!__all_sync(0xffffffff, ((pp[I][3] ^ tg) | (pp[I][7] ^ tg) | (pp[I][11] ^ tg) | (pp[I][15] ^ tg)) < 0x10000u)) { if (clock32() - t0 > TIMEOUT) break; LOAD_PART(I) } \
      _Pragma("unroll") for (int q = 0; q < 4; q++) { _Pragma("unroll") for (int e = 0; e < 7; e++) f[7 * q + e] += (e & 1) ? bf_hi(pp[I][4 * q + (e >> 1)]) : bf_lo(pp[I][4 * q + (e >> 1)]); } }
    const int orow = (128 * r + 64 * wg + 16 * w + g) * 224 + 112 * n + 28 * p + t;
    #pragma unroll
    for (int i = 0; i < 7; i++) { xr[2 * i] = __ldg(xg + orow + 4 * i); xr[2 * i + 1] = __ldg(xg + orow + 8 * 224 + 4 * i); }
    LOAD_PART(0)
    LOAD_PART(1)
    float f[28];
    const uint32_t dw = sb + (p & 1);
    batch_begin(c, 2, 0); PROF_T(28);
    rs56<0, 0, 14, 0>(dw + 2 * (SLOT >> 4), f, h); batch_mid(c, 2, 0); rs56<1, 0, 14, 0>(dw + 2 * (SLOT >> 4), f, hp); batch_end(c);
    LOAD_PART(2)
    wg_wait<0>(); fence_regs(f); PROF_T(29);
    ADD_PART(0)
    ADD_PART(1)
    ADD_PART(2)
    PROF_T(33);
    #pragma unroll
    for (int i = 0; i < 28; i++) f[i] = f[i] * rcp(1.f + ex2(f[i] * -LOG2E));
    {
      float acc[28];
      mbar_wait(bars + 8 * (B_OB + wg), 0, budget);
      batch_begin(c, 0, 1); PROF_T(30);
      const uint32_t ab = sb + wg * 3584;
      static_for<0, 14>([&](auto K) { constexpr int k = decltype(K)::value;
        wgmma_ss_n56_nt<desc_lo(XR + k * 256, 128), HI_O, desc_lo(k * 2048, 0), HI128, k ? 1 : 0>(acc, ab, dw); });
      PROF_T(44);
      batch_mid(c, 0, 1);
      PROF_T(45);
      static_for<0, 14>([&](auto K) { constexpr int k = decltype(K)::value;
        wgmma_ss_n56_nt<desc_lo(XR + (14 + k) * 256, 128), HI_O, desc_lo(SLOT + k * 2048, 0), HI128, 1>(acc, ab, dw); });
      wg_commit();
      if (wg == 0) bar_arrive(2, 256);
      PROF_T(41);
      wg_wait<0>(); fence_regs(acc); PROF_T(31);
      #pragma unroll
      for (int i = 0; i < 7; i++) {
        out[orow + 4 * i] = pack_bf16(fmaf(acc[4 * i], f[4 * i], bf_lo(xr[2 * i])), fmaf(acc[4 * i + 1], f[4 * i + 1], bf_hi(xr[2 * i])));
        out[orow + 8 * 224 + 4 * i] = pack_bf16(fmaf(acc[4 * i + 2], f[4 * i + 2], bf_lo(xr[2 * i + 1])), fmaf(acc[4 * i + 3], f[4 * i + 3], bf_hi(xr[2 * i + 1])));
      }
      PROF_T(32);
    }
  }
}

typedef CUresult (*PFN_encodeTiled_t)(CUtensorMap*, CUtensorMapDataType, cuuint32_t, void*, const cuuint64_t*, const cuuint64_t*, const cuuint32_t*,
                                      const cuuint32_t*, CUtensorMapInterleave, CUtensorMapSwizzle, CUtensorMapL2promotion, CUtensorMapFloatOOBfill);
static void make_map(PFN_encodeTiled_t enc, CUtensorMap* m, const void* ptr, uint64_t cols, uint64_t rows, uint32_t bc, uint32_t br, CUtensorMapSwizzle sw) {
  cuuint64_t gd[2] = {cols, rows}; cuuint64_t gs[1] = {cols * 2};
  cuuint32_t bd[2] = {bc, br}; cuuint32_t es[2] = {1, 1};
  enc(m, CU_TENSOR_MAP_DATA_TYPE_BFLOAT16, 2, const_cast<void*>(ptr), gd, gs, bd, es, CU_TENSOR_MAP_INTERLEAVE_NONE, sw,
      CU_TENSOR_MAP_L2_PROMOTION_L2_128B, CU_TENSOR_MAP_FLOAT_OOB_FILL_NONE);
}

extern "C" void kernel_launch(void* const* d_in, const int* in_sizes, int n_in, void* d_out, int out_size) {
  (void)in_sizes; (void)n_in; (void)out_size;
  void* fn = nullptr; cudaDriverEntryPointQueryResult st;
  cudaGetDriverEntryPoint("cuTensorMapEncodeTiled", &fn, cudaEnableDefault, &st);
  PFN_encodeTiled_t enc = (PFN_encodeTiled_t)fn;
  Maps m;
  make_map(enc, &m.x, d_in[0], 448, 2048, 64, 64, CU_TENSOR_MAP_SWIZZLE_128B);
  make_map(enc, &m.qkv, d_in[1], 1344, 448, 64, 224, CU_TENSOR_MAP_SWIZZLE_128B);
  make_map(enc, &m.wo, d_in[2], 448, 448, 64, 224, CU_TENSOR_MAP_SWIZZLE_128B);
  make_map(enc, &m.w1, d_in[4], 1792, 448, 32, 224, CU_TENSOR_MAP_SWIZZLE_64B);
  make_map(enc, &m.w3, d_in[5], 1792, 448, 32, 224, CU_TENSOR_MAP_SWIZZLE_64B);
  make_map(enc, &m.w2, d_in[6], 448, 1792, 64, 224, CU_TENSOR_MAP_SWIZZLE_128B);
  cudaFuncSetAttribute(fused_kernel, cudaFuncAttributeMaxDynamicSharedMemorySize, SMEM_BYTES);
  fused_kernel<<<128, 384, SMEM_BYTES, cudaStreamPerThread>>>(m, (const uint32_t*)d_in[0], (uint32_t*)d_out);
}
```

```cpp
#include <cuda_runtime.h>
#include <cuda.h>
#include <cuda_bf16.h>
#include <stdint.h>
#include <type_traits>

template <int OFF, int SC> __device__ __forceinline__ void wgmma_rs_n56(float (&d)[28], uint32_t a0, uint32_t a1, uint32_t a2, uint32_t a3, uint64_t b) {
  asm volatile("{\n.reg .pred p;\n.reg .b64 db;\nsetp.ne.b32 p, %34, 0;\nadd.s64 db, %32, %33;\n"
    "wgmma.mma_async.sync.aligned.m64n56k16.f32.bf16.bf16 {%0, %1, %2, %3, %4, %5, %6, %7, %8, %9, %10, %11, %12, %13, %14, %15, %16, %17, %18, %19, %20, %21, %22, %23, %24, %25, %26, %27}, {%28, %29, %30, %31}, db, p, 1, 1, 1;\n}\n"
    : "+f"(d[0]), "+f"(d[1]), "+f"(d[2]), "+f"(d[3]), "+f"(d[4]), "+f"(d[5]), "+f"(d[6]), "+f"(d[7]), "+f"(d[8]), "+f"(d[9]), "+f"(d[10]), "+f"(d[11]), "+f"(d[12]), "+f"(d[13]), "+f"(d[14]), "+f"(d[15]), "+f"(d[16]), "+f"(d[17]), "+f"(d[18]), "+f"(d[19]), "+f"(d[20]), "+f"(d[21]), "+f"(d[22]), "+f"(d[23]), "+f"(d[24]), "+f"(d[25]), "+f"(d[26]), "+f"(d[27])
    : "r"(a0), "r"(a1), "r"(a2), "r"(a3), "l"(b), "n"(OFF), "n"(SC));
}
template <int OFF, int SC> __device__ __forceinline__ void wgmma_rs_n64(float (&d)[32], uint32_t a0, uint32_t a1, uint32_t a2, uint32_t a3, uint64_t b) {
  asm volatile("{\n.reg .pred p;\n.reg .b64 db;\nsetp.ne.b32 p, %38, 0;\nadd.s64 db, %36, %37;\n"
    "wgmma.mma_async.sync.aligned.m64n64k16.f32.bf16.bf16 {%0, %1, %2, %3, %4, %5, %6, %7, %8, %9, %10, %11, %12, %13, %14, %15, %16, %17, %18, %19, %20, %21, %22, %23, %24, %25, %26, %27, %28, %29, %30, %31}, {%32, %33, %34, %35}, db, p, 1, 1, 1;\n}\n"
    : "+f"(d[0]), "+f"(d[1]), "+f"(d[2]), "+f"(d[3]), "+f"(d[4]), "+f"(d[5]), "+f"(d[6]), "+f"(d[7]), "+f"(d[8]), "+f"(d[9]), "+f"(d[10]), "+f"(d[11]), "+f"(d[12]), "+f"(d[13]), "+f"(d[14]), "+f"(d[15]), "+f"(d[16]), "+f"(d[17]), "+f"(d[18]), "+f"(d[19]), "+f"(d[20]), "+f"(d[21]), "+f"(d[22]), "+f"(d[23]), "+f"(d[24]), "+f"(d[25]), "+f"(d[26]), "+f"(d[27]), "+f"(d[28]), "+f"(d[29]), "+f"(d[30]), "+f"(d[31])
    : "r"(a0), "r"(a1), "r"(a2), "r"(a3), "l"(b), "n"(OFF), "n"(SC));
}
template <int OFFA, int OFFB, int SC> __device__ __forceinline__ void wgmma_ss_n64_tt(uint32_t* d, uint64_t a, uint64_t b) {
  asm volatile("{\n.reg .pred p;\n.reg .b64 da, db;\nsetp.ne.b32 p, %36, 0;\nadd.s64 da, %32, %34;\nadd.s64 db, %33, %35;\n"
    "wgmma.mma_async.sync.aligned.m64n64k16.f32.bf16.bf16 {%0, %1, %2, %3, %4, %5, %6, %7, %8, %9, %10, %11, %12, %13, %14, %15, %16, %17, %18, %19, %20, %21, %22, %23, %24, %25, %26, %27, %28, %29, %30, %31}, da, db, p, 1, 1, 1, 1;\n}\n"
    : "+r"(d[0]), "+r"(d[1]), "+r"(d[2]), "+r"(d[3]), "+r"(d[4]), "+r"(d[5]), "+r"(d[6]), "+r"(d[7]), "+r"(d[8]), "+r"(d[9]), "+r"(d[10]), "+r"(d[11]), "+r"(d[12]), "+r"(d[13]), "+r"(d[14]), "+r"(d[15]), "+r"(d[16]), "+r"(d[17]), "+r"(d[18]), "+r"(d[19]), "+r"(d[20]), "+r"(d[21]), "+r"(d[22]), "+r"(d[23]), "+r"(d[24]), "+r"(d[25]), "+r"(d[26]), "+r"(d[27]), "+r"(d[28]), "+r"(d[29]), "+r"(d[30]), "+r"(d[31])
    : "l"(a), "l"(b), "n"(OFFA), "n"(OFFB), "n"(SC));
}
template <int OFFA, int OFFB> __device__ __forceinline__ void wgmma_ss_n64_nt(uint32_t* d, uint64_t a, uint64_t b, uint32_t sc) {
  asm volatile("{\n.reg .pred p;\n.reg .b64 da, db;\nsetp.ne.b32 p, %36, 0;\nadd.s64 da, %32, %34;\nadd.s64 db, %33, %35;\n"
    "wgmma.mma_async.sync.aligned.m64n64k16.f32.bf16.bf16 {%0, %1, %2, %3, %4, %5, %6, %7, %8, %9, %10, %11, %12, %13, %14, %15, %16, %17, %18, %19, %20, %21, %22, %23, %24, %25, %26, %27, %28, %29, %30, %31}, da, db, p, 1, 1, 0, 1;\n}\n"
    : "+r"(d[0]), "+r"(d[1]), "+r"(d[2]), "+r"(d[3]), "+r"(d[4]), "+r"(d[5]), "+r"(d[6]), "+r"(d[7]), "+r"(d[8]), "+r"(d[9]), "+r"(d[10]), "+r"(d[11]), "+r"(d[12]), "+r"(d[13]), "+r"(d[14]), "+r"(d[15]), "+r"(d[16]), "+r"(d[17]), "+r"(d[18]), "+r"(d[19]), "+r"(d[20]), "+r"(d[21]), "+r"(d[22]), "+r"(d[23]), "+r"(d[24]), "+r"(d[25]), "+r"(d[26]), "+r"(d[27]), "+r"(d[28]), "+r"(d[29]), "+r"(d[30]), "+r"(d[31])
    : "l"(a), "l"(b), "n"(OFFA), "n"(OFFB), "r"(sc));
}
template <int OFFA, int OFFB> __device__ __forceinline__ void wgmma_ss_n112_nt(uint32_t* d, uint64_t a, uint64_t b, uint32_t sc) {
  asm volatile("{\n.reg .pred p;\n.reg .b64 da, db;\nsetp.ne.b32 p, %60, 0;\nadd.s64 da, %56, %58;\nadd.s64 db, %57, %59;\n"
    "wgmma.mma_async.sync.aligned.m64n112k16.f32.bf16.bf16 {%0, %1, %2, %3, %4, %5, %6, %7, %8, %9, %10, %11, %12, %13, %14, %15, %16, %17, %18, %19, %20, %21, %22, %23, %24, %25, %26, %27, %28, %29, %30, %31, %32, %33, %34, %35, %36, %37, %38, %39, %40, %41, %42, %43, %44, %45, %46, %47, %48, %49, %50, %51, %52, %53, %54, %55}, da, db, p, 1, 1, 0, 1;\n}\n"
    : "+r"(d[0]), "+r"(d[1]), "+r"(d[2]), "+r"(d[3]), "+r"(d[4]), "+r"(d[5]), "+r"(d[6]), "+r"(d[7]), "+r"(d[8]), "+r"(d[9]), "+r"(d[10]), "+r"(d[11]), "+r"(d[12]), "+r"(d[13]), "+r"(d[14]), "+r"(d[15]), "+r"(d[16]), "+r"(d[17]), "+r"(d[18]), "+r"(d[19]), "+r"(d[20]), "+r"(d[21]), "+r"(d[22]), "+r"(d[23]), "+r"(d[24]), "+r"(d[25]), "+r"(d[26]), "+r"(d[27]), "+r"(d[28]), "+r"(d[29]), "+r"(d[30]), "+r"(d[31]), "+r"(d[32]), "+r"(d[33]), "+r"(d[34]), "+r"(d[35]), "+r"(d[36]), "+r"(d[37]), "+r"(d[38]), "+r"(d[39]), "+r"(d[40]), "+r"(d[41]), "+r"(d[42]), "+r"(d[43]), "+r"(d[44]), "+r"(d[45]), "+r"(d[46]), "+r"(d[47]), "+r"(d[48]), "+r"(d[49]), "+r"(d[50]), "+r"(d[51]), "+r"(d[52]), "+r"(d[53]), "+r"(d[54]), "+r"(d[55])
    : "l"(a), "l"(b), "n"(OFFA), "n"(OFFB), "r"(sc));
}

#define DEVINL __device__ __forceinline__

constexpr int SLOT = 28672;
constexpr int XR = 114688;
constexpr int XR2 = XR + 57344;
constexpr int PK_OFF = XR;
constexpr int V_OFF = XR + 16384;
constexpr int KV_OFF = XR + 32768;
constexpr int KVS_OFF = XR + 40960;
constexpr int BARS = 229376;
constexpr int VAR_OFF = BARS + 512;
constexpr int SMEM_BYTES = VAR_OFF + 512;
constexpr int B_FULL = 96  , B_EMPTY = 4, B_XB = 8  , B_HB = 16  , B_XF = 20, B_EB = 21, B_KVB = 22,
              B_OF = 23  , B_FB = 27  , B_VAR = 31, B_PB = 32  , B_OB = 36  , B_SB = 38  , B_SF = 40  , B_X2 = 42, B_QB = 43  , B_NUM = 45;
constexpr uint32_t SB16 = 1024 >> 4;
constexpr int EPOCH_OFF = BARS + 384;

#define ABL 0
#define PFIRST 30
#define PORD 0x000b0a090800ull
#define W0LATE 0
#define W1EARLY 2
#define XFIRST 1
#define SCF 1
#define LORD 0xda8u
#define QLATE 1
#define PAE 0
#define HSUM 0
#define NBR 1
#define LALL 0
#define LNO 0
#define NA 4
#define OWN 0x50
#define QK 4
#define QW 0
#define SFIRST 0
#define LNS 0
#define NE 6
constexpr int OB = 5;
#define OSLP 400
#define NF 3
constexpr int NFIRST = NF;
__device__ float g_kv[2][8][56 * 32];
__device__ uint4 g_o[16][2][3584];
__device__ uint4 g_part[16][8][2][3][512];
__device__ unsigned g_cnt_kv[8 * 32];
__device__ unsigned g_cnt_o[16 * 2 * 32];
#define PROF_T(idx)
#define PROF_S(idx)
#define PROF_H(idx)
#define PROF_X(idx)

DEVINL uint32_t smem_u32(const void* p) { return (uint32_t)__cvta_generic_to_shared(p); }
DEVINL unsigned clock32() { unsigned c; asm volatile("mov.u32 %0, %%clock;" : "=r"(c)); return c; }
DEVINL void mbar_init(uint32_t bar, uint32_t cnt) { asm volatile("mbarrier.init.shared::cta.b64 [%0], %1;" :: "r"(bar), "r"(cnt) : "memory"); }
DEVINL void mbar_expect_tx(uint32_t bar, uint32_t bytes) { asm volatile("mbarrier.arrive.expect_tx.shared::cta.b64 _, [%0], %1;" :: "r"(bar), "r"(bytes) : "memory"); }
DEVINL void mbar_arrive(uint32_t bar) { asm volatile("mbarrier.arrive.shared::cta.b64 _, [%0];" :: "r"(bar) : "memory"); }
DEVINL uint32_t mapa(uint32_t addr, uint32_t cta) { uint32_t r; asm("mapa.shared::cluster.u32 %0, %1, %2;" : "=r"(r) : "r"(addr), "r"(cta)); return r; }
DEVINL void mbar_arrive_remote(uint32_t raddr) { asm volatile("mbarrier.arrive.shared::cluster.b64 _, [%0];" :: "r"(raddr) : "memory"); }
constexpr unsigned TIMEOUT = 1u << 30;
DEVINL void mbar_wait(uint32_t bar, uint32_t parity, int& budget) {
  asm volatile("{\n.reg .pred p, q;\nW_%=:\nmbarrier.try_wait.parity.shared::cta.b64 p, [%1], %2;\nadd.s32 %0, %0, -1;\nsetp.gt.and.s32 q, %0, 0, !p;\n@q bra W_%=;\n}"
    : "+r"(budget) : "r"(bar), "r"(parity) : "memory");
}
DEVINL unsigned ld_relaxed(const unsigned* p) { unsigned v; asm volatile("ld.relaxed.gpu.global.u32 %0, [%1];" : "=r"(v) : "l"(p) : "memory"); return v; }
DEVINL void poll_flag(const unsigned* p, unsigned target) {
  unsigned t0 = clock32();
  while ((int)(ld_relaxed(p) - target) < 0) { if (clock32() - t0 > TIMEOUT) break; __nanosleep(20); }
}
DEVINL void flag_add(unsigned* p, unsigned v) { asm volatile("red.relaxed.gpu.global.add.u32 [%0], %1;" :: "l"(p), "r"(v) : "memory"); }
DEVINL void bulk_store(void* dst, uint32_t src, uint32_t bytes) {
  asm volatile("cp.async.bulk.global.shared::cta.bulk_group [%0], [%1], %2;" :: "l"(dst), "r"(src), "r"(bytes) : "memory");
}
DEVINL void bulk_reduce_f32(void* dst, uint32_t src, uint32_t bytes) {
  asm volatile("cp.reduce.async.bulk.global.shared::cta.bulk_group.add.f32 [%0], [%1], %2;" :: "l"(dst), "r"(src), "r"(bytes) : "memory");
}
DEVINL void bulk_commit() { asm volatile("cp.async.bulk.commit_group;" ::: "memory"); }
DEVINL void bulk_wait_all() { asm volatile("cp.async.bulk.wait_group 0;" ::: "memory"); }
DEVINL void st_b128x4(uint4* p, const uint32_t (&v)[16]) {
  #pragma unroll
  for (int q = 0; q < 4; q++)
    asm volatile("st.relaxed.gpu.global.v4.b32 [%0], {%1, %2, %3, %4};" :: "l"(p + q * 128), "r"(v[4 * q]), "r"(v[4 * q + 1]), "r"(v[4 * q + 2]), "r"(v[4 * q + 3]) : "memory");
}
DEVINL void ld_b128(const uint4* p, uint32_t& a, uint32_t& b, uint32_t& c, uint32_t& d) {
  asm volatile("{\n.reg .b64 lo, hi;\n.reg .b128 v;\nld.relaxed.gpu.global.b128 v, [%4];\nmov.b128 {lo, hi}, v;\nmov.b64 {%0, %1}, lo;\nmov.b64 {%2, %3}, hi;\n}"
    : "=r"(a), "=r"(b), "=r"(c), "=r"(d) : "l"(p) : "memory");
}
DEVINL void lds128(uint32_t a, uint32_t* v) { asm volatile("ld.shared.v4.u32 {%0, %1, %2, %3}, [%4];" : "=r"(v[0]), "=r"(v[1]), "=r"(v[2]), "=r"(v[3]) : "r"(a) : "memory"); }
DEVINL float sqrt_approx(float x) { float r; asm("sqrt.approx.ftz.f32 %0, %1;" : "=f"(r) : "f"(x)); return r; }
DEVINL void tma_2d(uint32_t dst, const CUtensorMap* tm, int c0, int c1, uint32_t bar) {
  asm volatile("cp.async.bulk.tensor.2d.shared::cluster.global.mbarrier::complete_tx::bytes [%0], [%1, {%3, %4}], [%2];"
    :: "r"(dst), "l"(tm), "r"(bar), "r"(c0), "r"(c1) : "memory");
}
DEVINL void tma_3d(uint32_t dst, const CUtensorMap* tm, int c0, int c1, int c2, uint32_t bar) {
  asm volatile("cp.async.bulk.tensor.3d.shared::cluster.global.mbarrier::complete_tx::bytes [%0], [%1, {%3, %4, %5}], [%2];"
    :: "r"(dst), "l"(tm), "r"(bar), "r"(c0), "r"(c1), "r"(c2) : "memory");
}
DEVINL void bulk_load(uint32_t dst, const void* src, uint32_t bytes, uint32_t bar) {
  asm volatile("cp.async.bulk.shared::cluster.global.mbarrier::complete_tx::bytes [%0], [%1], %2, [%3];"
    :: "r"(dst), "l"(src), "r"(bytes), "r"(bar) : "memory");
}
DEVINL void wg_fence() { asm volatile("wgmma.fence.sync.aligned;" ::: "memory"); }
DEVINL void wg_commit() { asm volatile("wgmma.commit_group.sync.aligned;" ::: "memory"); }
template <int N> DEVINL void wg_wait() { asm volatile("wgmma.wait_group.sync.aligned %0;" :: "n"(N) : "memory"); }
__host__ __device__ constexpr int desc_lo(int off, int lbo) { return (off >> 4) | ((lbo >> 4) << 16); }
__host__ __device__ constexpr uint32_t desc_hi(int sbo, uint32_t swz) { return (uint32_t)(sbo >> 4) | (swz << 30); }
constexpr uint32_t HI128 = desc_hi(1024, 1), HI64 = desc_hi(512, 2), HI_O = desc_hi(3584, 0);
template <int I, int N, class F> DEVINL void static_for(F&& f) { if constexpr (I < N) { f(std::integral_constant<int, I>{}); static_for<I + 1, N>(f); } }
DEVINL void bar_sync(int id, int n) { asm volatile("bar.sync %0, %1;" :: "r"(id), "r"(n) : "memory"); }
DEVINL void bar_arrive(int id, int n) { asm volatile("bar.arrive %0, %1;" :: "r"(id), "r"(n) : "memory"); }
DEVINL void fence_async() { asm volatile("fence.proxy.async.shared::cta;" ::: "memory"); }
DEVINL uint32_t pack_bf16(float lo, float hi) { uint32_t r; asm("cvt.rn.bf16x2.f32 %0, %1, %2;" : "=r"(r) : "f"(hi), "f"(lo)); return r; }
DEVINL float bf_lo(uint32_t v) { return __uint_as_float(v << 16); }
DEVINL float bf_hi(uint32_t v) { return __uint_as_float(v & 0xffff0000u); }
DEVINL float round_bf16(float x) { return bf_lo(pack_bf16(x, 0.f) & 0xffffu); }
DEVINL float ex2(float x) { float e; asm("ex2.approx.ftz.f32 %0, %1;" : "=f"(e) : "f"(x)); return e; }
DEVINL float tanh_hw(float x) { float r; asm("tanh.approx.f32 %0, %1;" : "=f"(r) : "f"(x)); return r; }
DEVINL float rcp(float x) { float r; asm("rcp.approx.ftz.f32 %0, %1;" : "=f"(r) : "f"(x)); return r; }
template <int N> DEVINL void fence_regs(float (&d)[N]) {
  #pragma unroll
  for (int i = 0; i < N; i++) asm volatile("" : "+f"(d[i]) :: "memory");
}
DEVINL void ldsm4(uint32_t addr, uint32_t& a0, uint32_t& a1, uint32_t& a2, uint32_t& a3) {
  asm volatile("ldmatrix.sync.aligned.m8n8.x4.shared.b16 {%0, %1, %2, %3}, [%4];" : "=r"(a0), "=r"(a1), "=r"(a2), "=r"(a3) : "r"(addr) : "memory");
}
DEVINL void stsm4(uint32_t addr, uint32_t a0, uint32_t a1, uint32_t a2, uint32_t a3) {
  asm volatile("stmatrix.sync.aligned.m8n8.x4.shared.b16 [%0], {%1, %2, %3, %4};" :: "r"(addr), "r"(a0), "r"(a1), "r"(a2), "r"(a3) : "memory");
}
DEVINL void mma16816(float (&c)[4], const uint32_t* a, uint32_t b0, uint32_t b1) {
  asm volatile("mma.sync.aligned.m16n8k16.row.col.f32.bf16.bf16.f32 {%0, %1, %2, %3}, {%4, %5, %6, %7}, {%8, %9}, {%0, %1, %2, %3};"
    : "+f"(c[0]), "+f"(c[1]), "+f"(c[2]), "+f"(c[3]) : "r"(a[0]), "r"(a[1]), "r"(a[2]), "r"(a[3]), "r"(b0), "r"(b1));
}
DEVINL uint32_t add_bf16x2(uint32_t a, uint32_t b) { uint32_t r; asm("add.rn.bf16x2 %0, %1, %2;" : "=r"(r) : "r"(a), "r"(b)); return r; }
template <int N> DEVINL void undef_regs(uint32_t (&d)[N]) {
  #pragma unroll
  for (int i = 0; i < N; i++) asm volatile("" : "=r"(d[i]));
}
DEVINL uint32_t sub_bf16x2(uint32_t a, uint32_t b) { uint32_t r; asm("sub.rn.bf16x2 %0, %1, %2;" : "=r"(r) : "r"(a), "r"(b)); return r; }
DEVINL void st_async4(uint32_t raddr, uint32_t a0, uint32_t a1, uint32_t a2, uint32_t a3, uint32_t rbar) {
  asm volatile("st.async.weak.shared::cluster.mbarrier::complete_tx::bytes.v4.b32 [%0], {%1, %2, %3, %4}, [%5];"
    :: "r"(raddr), "r"(a0), "r"(a1), "r"(a2), "r"(a3), "r"(rbar) : "memory");
}
constexpr float LOG2E = 1.4426950408889634f;

DEVINL float phi(float a, float r, float rl) {
  float e; asm("add.rn.ftz.sat.f32 %0, %1, %2;" : "=f"(e) : "f"(ex2(a * rl)), "f"(1e-6f));
  return fmaxf(fmaf(a, r, 1.000001f), e);
}

DEVINL void h_place(uint32_t (&h)[56], int c) {
  asm volatile("{\nts_%=: .branchtargets L0_%=, L1_%=, L2_%=, L3_%=, L4_%=, L5_%=;\nbrx.idx.uni %56, ts_%=;\n"
    "L0_%=:\nmov.b32 %0, %48;\nmov.b32 %1, %49;\nmov.b32 %2, %50;\nmov.b32 %3, %51;\nmov.b32 %4, %52;\nmov.b32 %5, %53;\nmov.b32 %6, %54;\nmov.b32 %7, %55;\nbra.uni E_%=;\n"
    "L1_%=:\nmov.b32 %8, %48;\nmov.b32 %9, %49;\nmov.b32 %10, %50;\nmov.b32 %11, %51;\nmov.b32 %12, %52;\nmov.b32 %13, %53;\nmov.b32 %14, %54;\nmov.b32 %15, %55;\nbra.uni E_%=;\n"
    "L2_%=:\nmov.b32 %16, %48;\nmov.b32 %17, %49;\nmov.b32 %18, %50;\nmov.b32 %19, %51;\nmov.b32 %20, %52;\nmov.b32 %21, %53;\nmov.b32 %22, %54;\nmov.b32 %23, %55;\nbra.uni E_%=;\n"
    "L3_%=:\nmov.b32 %24, %48;\nmov.b32 %25, %49;\nmov.b32 %26, %50;\nmov.b32 %27, %51;\nmov.b32 %28, %52;\nmov.b32 %29, %53;\nmov.b32 %30, %54;\nmov.b32 %31, %55;\nbra.uni E_%=;\n"
    "L4_%=:\nmov.b32 %32, %48;\nmov.b32 %33, %49;\nmov.b32 %34, %50;\nmov.b32 %35, %51;\nmov.b32 %36, %52;\nmov.b32 %37, %53;\nmov.b32 %38, %54;\nmov.b32 %39, %55;\nbra.uni E_%=;\n"
    "L5_%=:\nmov.b32 %40, %48;\nmov.b32 %41, %49;\nmov.b32 %42, %50;\nmov.b32 %43, %51;\nmov.b32 %44, %52;\nmov.b32 %45, %53;\nmov.b32 %46, %54;\nmov.b32 %47, %55;\n"
    "E_%=:\n}"
    : "+r"(h[0]), "+r"(h[1]), "+r"(h[2]), "+r"(h[3]), "+r"(h[4]), "+r"(h[5]), "+r"(h[6]), "+r"(h[7]), "+r"(h[8]), "+r"(h[9]), "+r"(h[10]), "+r"(h[11]), "+r"(h[12]), "+r"(h[13]), "+r"(h[14]), "+r"(h[15]), "+r"(h[16]), "+r"(h[17]), "+r"(h[18]), "+r"(h[19]), "+r"(h[20]), "+r"(h[21]), "+r"(h[22]), "+r"(h[23]), "+r"(h[24]), "+r"(h[25]), "+r"(h[26]), "+r"(h[27]), "+r"(h[28]), "+r"(h[29]), "+r"(h[30]), "+r"(h[31]), "+r"(h[32]), "+r"(h[33]), "+r"(h[34]), "+r"(h[35]), "+r"(h[36]), "+r"(h[37]), "+r"(h[38]), "+r"(h[39]), "+r"(h[40]), "+r"(h[41]), "+r"(h[42]), "+r"(h[43]), "+r"(h[44]), "+r"(h[45]), "+r"(h[46]), "+r"(h[47])
    : "r"(h[48]), "r"(h[49]), "r"(h[50]), "r"(h[51]), "r"(h[52]), "r"(h[53]), "r"(h[54]), "r"(h[55]), "r"(c));
}
struct Ctx { int wg; int budget; };

DEVINL void tile_wait(Ctx& c, uint32_t bf) { mbar_wait(bf + 8 * B_FULL, 0, c.budget); }
DEVINL void batch_begin(Ctx& c) { bar_sync(1 + c.wg, 256); }
DEVINL void batch_mid(Ctx& c, uint32_t bf) {
  wg_commit();
  mbar_wait(bf + 8 * (B_FULL + 1), 0, c.budget);
}
template <int N> DEVINL void wait_release(uint32_t bar) {
  asm volatile("{\n.reg .pred p;\nelect.sync _|p, 0xffffffff;\nwgmma.wait_group.sync.aligned %1;\n@p mbarrier.arrive.shared::cta.b64 _, [%0];\n}" :: "r"(bar), "n"(N) : "memory");
}
DEVINL void warp_arrive(uint32_t bar) {
  asm volatile("{\n.reg .pred p;\nelect.sync _|p, 0xffffffff;\n@p mbarrier.arrive.shared::cta.b64 _, [%0];\n}" :: "r"(bar) : "memory");
}
DEVINL void batch_rel_lo(uint32_t bs) {
  wg_commit();
  wait_release<1>(bs + 8 * B_EMPTY);
}
DEVINL void batch_end(Ctx& c) {
  wg_commit();
  bar_arrive(1 + (c.wg ^ 1), 256);
}
DEVINL void batch_rel_hi(uint32_t bs) {
  wait_release<0>(bs + 8 * (B_EMPTY + 1));
}
template <int KIND, int HALF, int K0, int K1, int NC> DEVINL void rs(uint64_t d, float (&acc)[NC], const uint32_t* a) {
  static_for<K0, K1>([&](auto K) { constexpr int k = decltype(K)::value; constexpr int SC = (HALF | k | (KIND & 2)) ? 1 : 0;
    if constexpr (KIND == 1) wgmma_rs_n64<desc_lo(HALF * SLOT + k * 1024, 14336), SC>(acc, a[4 * k], a[4 * k + 1], a[4 * k + 2], a[4 * k + 3], d);
    else wgmma_rs_n56<desc_lo(HALF * SLOT + k * 2048, 0), SC>(acc, a[4 * k], a[4 * k + 1], a[4 * k + 2], a[4 * k + 3], d); });
}
template <int KIND, int NC> DEVINL void mma_hi(Ctx& c, uint32_t bs, uint64_t d, float (&acc)[NC], const uint32_t* a) {
  wg_fence();
  rs<KIND, 1, 0, 4>(d, acc, a); batch_rel_lo(bs);
  rs<KIND, 1, 4, 14>(d, acc, a); batch_end(c);
}
DEVINL int cta_map(uint32_t i) {
  const bool b2 = i & 4, b3 = i & 8, b4 = i & 16, b5 = i & 32;
  const uint32_t lo = b4 ? (b3 ? (b2 ? 0x1715070du : 0x36342624u) : (b2 ? 0x1614060cu : 0x33312321u)) : (b3 ? (b2 ? 0x13110309u : 0x32302220u) : (b2 ? 0x12100208u : 0x05040100u));
  const uint32_t hi = b4 ? (b3 ? (b2 ? 0x3f3d2f2du : 0x1f1d0f3eu) : (b2 ? 0x3c2e2c1eu : 0x1c0e3b39u)) : (b3 ? (b2 ? 0x2b291b19u : 0x0b3a382au) : (b2 ? 0x281a180au : 0x37352725u));
  return ((b5 ? hi : lo) >> (8 * (i & 3))) & 255;
}
struct Maps { CUtensorMap x2, x, w1, w3, qkv, w2, wo; };

DEVINL void tile_load(const Maps& m, int t, int n, int p, uint32_t dst, uint32_t fb) {
  const int b = t >> 1, hf = t & 1, j = 2 * p + n;
  mbar_expect_tx(fb, SLOT);
  if (b >= 3 && b < 10) {
    tma_2d(dst, &m.w1, 224 * j + 32 * (b - 3), 224 * hf, fb);
    tma_2d(dst + 14336, &m.w3, 224 * j + 32 * (b - 3), 224 * hf, fb);
  } else if (b >= 10 && b != 13) {
    tma_2d(dst, &m.w2, 112 * (p ^ (b < 13 ? 13 - b : 0)) + 48 * n, 224 * (j ^ hf), fb);
  } else if (b == 13) {
    tma_2d(dst, &m.wo, 112 * p, 224 * n + 112 * hf, fb);
    tma_2d(dst + 14336, &m.wo, 112 * p + 64, 224 * n + 112 * hf, fb);
  } else {
    const int c0 = (b < 2 ? 448 * (b + 1) : 0) + 56 * j - 8 * n;
    tma_2d(dst + n * 14336, &m.qkv, c0, 224 * hf + 112 * n, fb);
    tma_2d(dst + (n ^ 1) * 14336, &m.qkv, c0, 224 * hf + 112 * (n ^ 1), fb);
  }
}
DEVINL void x_load(const Maps& m, int row, uint32_t dst, uint32_t bar) {
  #pragma unroll
  for (int q = 0; q < 3; q++) { mbar_expect_tx(bar + 8 * q, 16384); tma_3d(dst + q * 16384, &m.x2, 0, row, 2 * q, bar + 8 * q); }
  mbar_expect_tx(bar + 24, 8192); tma_2d(dst + 49152, &m.x, 384, row, bar + 24);
}

__global__ void __cluster_dims__(2, 1, 1) __launch_bounds__(384, 1)
fused_kernel(const __grid_constant__ Maps maps, uint4* __restrict__ out, const uint64_t d128, const uint64_t d64, const uint64_t dO, const uint32_t zero) {
  extern __shared__ __align__(1024) uint8_t smem_raw[];
  const uint32_t base = smem_u32(smem_raw);
  const uint32_t bars = base + BARS;
  const int warp = __shfl_sync(0xffffffff, threadIdx.x >> 5, 0), lane = threadIdx.x & 31;
  const int cidx = cta_map(blockIdx.x >> 1);
  const int n = blockIdx.x & 1, p = cidx & 3, r = cidx >> 2, j = 2 * p + n;
  if ((base & 0x3FFFF) != SB16 * 16) return;

  if (warp > 7) asm volatile("setmaxnreg.dec.sync.aligned.u32 40;");
  if (warp == 8) {
    if (lane == 0) {
      PROF_H(0);
      #pragma unroll
      for (int i = 0; i < 8; i++) mbar_init(bars + 8 * (B_XB + i), 1);
      #pragma unroll
      for (int i = 0; i < 4; i++) mbar_init(bars + 8 * (B_FULL + i), 1);
      fence_async();
    }
    __syncwarp();
    bar_arrive(3, 384);
    asm volatile("barrier.cluster.arrive.relaxed.aligned;" ::: "memory");
    if (lane == 0) {
      PROF_H(59);
      x_load(maps, r * 128, base + XR, bars + 8 * B_XB);
      PROF_H(32);
      x_load(maps, r * 128 + 64, base + XR2, bars + 8 * (B_XB + 4));
      PROF_H(34);
      #pragma unroll 1
      for (int t = 0; t < NFIRST; t++) tile_load(maps, t, n, p, base + t * SLOT, bars + 8 * (B_FULL + t));
      PROF_H(33);
    }
    __syncwarp();
  } else if (warp == 10) {
    if (lane >= 4 && lane < 30) mbar_init(bars + 8 * (B_FULL + lane), 1);
    if (lane == 0) {
      #pragma unroll
      for (int i = B_EMPTY; i < B_NUM; i++) {
        if (i >= B_XB && i < B_HB) continue;
        mbar_init(bars + 8 * i, i >= B_QB ? 1 : i >= B_SF ? 4 : i == B_OB || i == B_OB + 1 ? 2 : i >= B_VAR ? 1 : i < B_XB || i == B_OF + 1 ? 8 : i >= B_FB || i == B_XF ? 4 : i == B_KVB || i == B_OF ? 2 : 1);
      }
      #pragma unroll
      for (int i = 0; i < 4; i++) mbar_expect_tx(bars + 8 * (B_HB + i), (i & 1) ? 4096 : 24576);
      mbar_expect_tx(bars + 8 * B_VAR, 256);
      mbar_expect_tx(bars + 8 * B_SB, 7168); mbar_expect_tx(bars + 8 * (B_SB + 1), 7168);
    }
    asm volatile("fence.mbarrier_init.release.cluster;" ::: "memory");
    fence_async();
  } else if (warp == 11 && lane < 7) {
    asm volatile("prefetch.tensormap [%0];" :: "l"(&maps.x2 + lane) : "memory");
  }
  __syncwarp();

  if (warp > 7) {
    int budget = 1 << 22;
    if (warp == 8) {
      bar_sync(4, 64);
    } else {
      asm volatile("barrier.cluster.arrive.relaxed.aligned;" ::: "memory");
      unsigned epoch;
      if (warp == 10) bar_arrive(4, 64);
      bar_sync(3, 384);
      if (warp == 9) {
        asm volatile("ld.relaxed.gpu.global.u32 %0, [%1];" : "=r"(epoch) : "l"(&g_cnt_kv[j * 32]) : "memory");
        epoch &= ~127u;
        if (lane == 0) {
          asm volatile("st.shared.v2.u32 [%0], {%1, %2};" :: "r"(base + EPOCH_OFF), "r"(epoch), "r"(0x40000000u | ((epoch << 9) & 0x1fff0000u)) : "memory");
          mbar_arrive(bars + 8 * B_EB);
        }
        if (lane < 28) reinterpret_cast<float4*>(&g_kv[((epoch >> 7) & 1) ^ 1][j][0])[r * 28 + lane] = make_float4(0.f, 0.f, 0.f, 0.f);
      }
    }
    asm volatile("barrier.cluster.wait.acquire.aligned;" ::: "memory");
    if (warp == 8) {
      if (lane == 0) {
        #pragma unroll 1
        for (int t = NFIRST; t < 30; t++) {
          const int slot = t & 3;
          mbar_wait(bars + 8 * (t < 4 ? B_FULL : B_EMPTY + slot), t < 4 ? 0 : ((t >> 2) & 1) ^ 1, budget);
          if (t < PFIRST) tile_load(maps, t, n, p, base + slot * SLOT, bars + 8 * (B_FULL + t));
          if (t >= 24) {
            if (t == 24) mbar_wait(bars + 8 * (B_OF + 1), 0, budget);
            #pragma unroll 1
            for (uint32_t m = (uint32_t)(PORD >> (8 * (t - 24))) & 255; m; m >>= 4) {
              const int w = m & 1, q = (m >> 1) & 1;
              const uint32_t pb = bars + 8 * (q ? B_PB + 2 * w : B_QB + w);
              mbar_expect_tx(pb, 8192);
              bulk_load(base + XR2 + w * 16384 + q * 8192, &g_part[r][q ? j : j ^ 2][w][q][0], 8192, pb);
            }
          }
          if (t >= PFIRST) tile_load(maps, t, n, p, base + slot * SLOT, bars + 8 * (B_FULL + t));
          PROF_H(2 + t);
        }
        mbar_wait(bars + 8 * B_SF, 0, budget);
        #pragma unroll 1
        for (uint32_t m = LORD; m; m >>= 4) {
          const int w = m & 3;
          if (m & 4) mbar_wait(bars + 8 * (B_SF + 1), 0, budget);
          if (w < 2) {
            mbar_expect_tx(bars + 8 * (B_PB + 2 * w + 1), 8192);
            bulk_load(base + XR + w * (57344 + 49152), &g_part[r][j][w][2][0], 8192, bars + 8 * (B_PB + 2 * w + 1));
            PROF_H(60 + w);
          } else {
            mbar_expect_tx(bars + 8 * B_XB, 16384);
            tma_2d(base + XR + 8192, &maps.x, 56 * j - 8 * n, r * 128, bars + 8 * B_XB);
            tma_2d(base + XR + 16384, &maps.x, 56 * j - 8 * n, r * 128 + 64, bars + 8 * B_XB);
          }
        }
      }
    } else {
      mbar_wait(bars + 8 * B_EB, 0, budget);
      unsigned epoch; asm volatile("ld.shared.u32 %0, [%1];" : "=r"(epoch) : "r"(base + EPOCH_OFF) : "memory");
      if (warp == 11) {
        if (lane == 0) {
          #pragma unroll 1
          for (int w = 0; w < 2; w++) {
            mbar_wait(bars + 8 * (B_FB + w), 0, budget);
            fence_async();
            bulk_reduce_f32(&g_kv[(epoch >> 7) & 1][j][0], base + KVS_OFF + w * 8192, 7168);
            bulk_commit();
          }
          bulk_wait_all();
          flag_add(&g_cnt_kv[j * 32], 8);
          PROF_H(40);
          #pragma unroll 1
          for (int w = 0; w < 2; w++) {
            mbar_wait(bars + 8 * (B_FB + 2 + w), 0, budget);
            fence_async();
            #pragma unroll 1
            for (int q = 0; q < 8; q++) bulk_store(&g_o[r][w][(((j >> 2) * 8 + q) * 28 + 7 * (j & 3)) * 8], base + V_OFF + w * 8192 + q * 896, 896);
            bulk_commit();
            bulk_wait_all();
            flag_add(&g_cnt_o[(r * 2 + w) * 32], 16);
            mbar_arrive(bars + 8 * (B_OF + 0));
            PROF_H(41 + w);
          }
        }
      } else {
        const unsigned target = epoch + 128;
        const int wsel = warp - 9;
        mbar_wait(bars + 8 * (B_FB + 0), 0, budget);
        #pragma unroll 1
        for (int it = 0; it < 8; it++) {
          const uint32_t a = base + KV_OFF + (it * 8 + wsel * 4) * 128 + lane * 16;
          asm volatile("st.shared.v4.u32 [%0], {%1, %1, %1, %1};" :: "r"(a), "r"(0) : "memory");
        }
        bar_sync(4, 64);
        if (lane == 0) poll_flag(&g_cnt_kv[j * 32], target);
        PROF_H(44);
        __syncwarp();
        {
          const float4* src = reinterpret_cast<const float4*>(&g_kv[(epoch >> 7) & 1][j][0]) + wsel * 32 + lane;
          float4 v[7];
          #pragma unroll
          for (int it = 0; it < 7; it++) asm volatile("ld.global.cg.v4.f32 {%0, %1, %2, %3}, [%4];" : "=f"(v[it].x), "=f"(v[it].y), "=f"(v[it].z), "=f"(v[it].w) : "l"(src + it * 64) : "memory");
          const int g = lane >> 2, t = lane & 3;
          #pragma unroll
          for (int it = 0; it < 7; it++) {
            const bool hd = it < 3 ? false : it > 3 ? true : g >= 4;
            const uint32_t row = base + KV_OFF + (it * 8 + g) * 128 + t * 4;
            const int ca = (hd ? 4 : 0) + 2 * wsel;
            asm volatile("st.shared.u32 [%0], %1;" :: "r"(row + ((ca ^ g) << 4)), "r"(pack_bf16(v[it].x, v[it].y)) : "memory");
            const bool zc = wsel && hd != (t >= 2);
            const uint32_t pz = pack_bf16(v[it].z, v[it].w);
            if (!zc) asm volatile("st.shared.u32 [%0], %1;" :: "r"(row + (((wsel ? 3 : ca + 1) ^ g) << 4)), "r"(pz) : "memory");
            else if (!(t & 1)) asm volatile("st.shared.u32 [%0], %1;" :: "r"(row - t * 4 + ((7 ^ g) << 4)), "r"(hd ? pz << 16 : pz) : "memory");
          }
        }
        fence_async();
        __syncwarp();
        if (lane == 0) {
          mbar_arrive(bars + 8 * B_KVB);
          if (warp == 9) {
            PROF_H(53);
          } else {
            mbar_wait(bars + 8 * B_OF, 0, budget);
            #pragma unroll 1
            for (int q = 0; q < 4; q++) {
              const int w = q >> 1;
              if (!(q & 1)) poll_flag(&g_cnt_o[(r * 2 + w) * 32], target);
              PROF_H(57 + w);
              if (ABL & 32) { mbar_arrive(bars + 8 * (B_OB + w)); continue; }
              mbar_expect_tx(bars + 8 * (B_OB + w), 14336);
              bulk_load(base + XR + q * 14336, &g_o[r][w][n * 1792 + (q & 1) * 896], 14336, bars + 8 * (B_OB + w));
              if (OSLP) __nanosleep(OSLP);
            }
          }
        }
      }
    }
  } else {
    asm volatile("barrier.cluster.arrive.relaxed.aligned;" ::: "memory");
    asm volatile("setmaxnreg.inc.sync.aligned.u32 232;");
    const int wg = warp >> 2, w = warp & 3, tid = threadIdx.x & 127;
    const int g = lane >> 2, t = lane & 3;
    Ctx c; c.wg = wg; c.budget = 1 << 22;
    int& budget = c.budget;
    bar_sync(3, 384);
    uint32_t a[112];
    const uint32_t frag_off = (16 * w + (lane & 7) + ((lane >> 3) & 1) * 8) * 128 + (((lane >> 4) ^ (lane & 7)) << 4);
    float r0, r1;
    uint32_t mb0, mb1;
    {
      float s[NA][4], q0[NA][4], q1[NA][4];
      #pragma unroll
      for (int q = 0; q < NA; q++)
        #pragma unroll
        for (int e = 0; e < 4; e++) s[q][e] = q0[q][e] = q1[q][e] = 0.f;
      const uint32_t xb = base + XR + wg * 57344;
      uint32_t c0, c1;
      PROF_T(0);
#define LN_LOAD(Q) { mbar_wait(bars + 8 * (B_XB + 4 * wg + (Q)), 0, budget); PROF_X(34 + (Q)); \
        _Pragma("unroll") for (int k = 8 * (Q); k < 8 * (Q) + 8 && k < 28; k++) ldsm4(xb + (k >> 2) * 8192 + (frag_off ^ ((k & 3) * 32)), a[4 * k], a[4 * k + 1], a[4 * k + 2], a[4 * k + 3]); }
#define LN_SUM(K0, K1) { if (wg == n) { _Pragma("unroll") for (int k = K0; k < K1; k++) { \
          mma16816(s[k % NA], a + 4 * k, 0x3F803F80u, 0x3F803F80u); \
          mma16816(q0[k % NA], a + 4 * k, sub_bf16x2(a[4 * k], c0), sub_bf16x2(a[4 * k + 2], c0)); \
          mma16816(q1[k % NA], a + 4 * k, sub_bf16x2(a[4 * k + 1], c1), sub_bf16x2(a[4 * k + 3], c1)); } } \
        else { _Pragma("unroll") for (int k = K0; k < K1; k++) mma16816(s[k % NA], a + 4 * k, 0x3F803F80u, 0x3F803F80u); } }
      mbar_wait(bars + 8 * (B_XB + 4 * wg), 0, budget);
      asm volatile("ld.shared.u16 %0, [%1];" : "=r"(c0) : "r"(xb + (16 * w + g) * 128 + g * 16) : "memory");
      asm volatile("ld.shared.u16 %0, [%1];" : "=r"(c1) : "r"(xb + (16 * w + g) * 128 + g * 16 + 1024) : "memory");
      #pragma unroll
      for (int k = 0; k < 8; k++) ldsm4(xb + (k >> 2) * 8192 + (frag_off ^ ((k & 3) * 32)), a[4 * k], a[4 * k + 1], a[4 * k + 2], a[4 * k + 3]);
      c0 *= 0x10001u; c1 *= 0x10001u;
      LN_LOAD(1) LN_SUM(0, 8) LN_LOAD(2) LN_SUM(8, 16) LN_LOAD(3) LN_SUM(16, 28)
      #pragma unroll
      for (int q = 2; q < NA; q++)
        #pragma unroll
        for (int e = 0; e < 4; e++) { s[q & 1][e] += s[q][e]; q0[q & 1][e] += q0[q][e]; q1[q & 1][e] += q1[q][e]; }
      asm volatile("{\n.reg .pred p;\nsetp.ne.b32 p, %2, 0;\n@p st.shared.f32 [%0], %1;\n@p bar.arrive 1, 256;\n}" :: "r"(bars + 400), "f"((q1[1][0] + s[1][0]) + (q1[0][0] + q0[0][0]) + (q0[1][0] + s[0][0])), "r"(wg) : "memory");
      PROF_T(57);
      const float m0 = (s[0][0] + s[1][0]) * (1.f / 448.f), m1 = (s[0][2] + s[1][2]) * (1.f / 448.f);
      const bool odd = g & 1;
      r0 = (odd ? q0[0][1] + q0[1][1] : q0[0][0] + q0[1][0]) * (1.f / 448.f) - m0 * (m0 - bf_hi(c0));
      r1 = (odd ? q1[0][3] + q1[1][3] : q1[0][2] + q1[1][2]) * (1.f / 448.f) - m1 * (m1 - bf_hi(c1));
      mb0 = pack_bf16(m0, m0); mb1 = pack_bf16(m1, m1);
      #pragma unroll
      for (int i = 0; i < 56; i++) a[i] = sub_bf16x2(a[i], (i & 1) ? mb1 : mb0);
    }
    auto ln_rest = [&]() {
      #pragma unroll
      for (int i = 56; i < 112; i++) a[i] = sub_bf16x2(a[i], (i & 1) ? mb1 : mb0);
      const float v0 = fmaxf(__shfl_sync(0xffffffff, r0, (lane & ~3) | (g >> 1)), 0.f), v1 = fmaxf(__shfl_sync(0xffffffff, r1, (lane & ~3) | (g >> 1)), 0.f);
      r0 = rcp(round_bf16(sqrt_approx(round_bf16(round_bf16(v0) + 1e-5f))));
      r1 = rcp(round_bf16(sqrt_approx(round_bf16(round_bf16(v1) + 1e-5f))));
    };
    auto ln_send = [&]() {
      asm volatile("barrier.cluster.wait.acquire.aligned;" ::: "memory");
      if (wg == 1 && lane == 0) mbar_arrive_remote(mapa(bars + 8 * B_XF, n ^ 1));
      if (wg == n && t == 0)
        asm volatile("st.async.weak.shared::cluster.mbarrier::complete_tx::bytes.v2.f32 [%0], {%1, %2}, [%3];"
          :: "r"(mapa(base + VAR_OFF + (8 * w + g) * 8, n ^ 1)), "f"(r0), "f"(r1), "r"(mapa(bars + 8 * B_VAR, n ^ 1)) : "memory");
    };
    if (LNS == 0 || (LNS == 2 && wg == 1)) { ln_rest(); ln_send(); }
    PROF_T(1);
    const uint32_t tile_off = wg * 8192 + frag_off;
    static_for<0, 3>([&](auto BB) {
      constexpr int b = decltype(BB)::value, sp = 2 * (b & 1);
      const uint64_t d = d128 + (sp * (SLOT >> 4) + n + (b == 2 ? zero : 0));
      const uint32_t bs = bars + 8 * sp;
      PROF_S(38 + b);
      tile_wait(c, bars + 16 * b);
      batch_begin(c); PROF_S(2 + 2 * b);
      float acc[28];
      if constexpr (b == 2) {
        uint32_t kv[32];
        const uint64_t kb = d128 + wg * 512;
        wg_fence();
        static_for<0, 4>([&](auto K) { constexpr int k = decltype(K)::value;
          wgmma_ss_n64_tt<desc_lo(PK_OFF + k * 2048, 0), desc_lo(V_OFF + k * 2048, 0), k ? 1 : 0>(kv, kb, kb); });
        wg_commit();
        wg_fence();
        rs<0, 0, 0, 14>(d, acc, a);
        wg_commit(); wg_wait<1>();
        #pragma unroll
        for (int i = 0; i < 32; i++) asm volatile("" : "+r"(kv[i]) :: "memory");
        #pragma unroll
        for (int hf = 0; hf < 2; hf++) {
          const bool hd = 16 * w + g + 8 * hf >= 28, v3 = hd == (t >= 2);
          const uint32_t sa = base + KVS_OFF + wg * 8192 + (2 * w + hf) * 1024 + lane * 16;
          const uint32_t* k0 = kv + 2 * hf;
          asm volatile("st.shared.v4.u32 [%0], {%1, %2, %3, %4};" :: "r"(sa), "r"(hd ? k0[16] : k0[0]), "r"(hd ? k0[17] : k0[1]), "r"(hd ? k0[20] : k0[4]), "r"(hd ? k0[21] : k0[5]) : "memory");
          asm volatile("st.shared.v4.u32 [%0], {%1, %2, %3, %4};" :: "r"(sa + 512), "r"(hd ? k0[24] : k0[8]), "r"(hd ? k0[25] : k0[9]), "r"(v3 ? k0[12] : k0[28]), "r"(v3 ? k0[13] : k0[29]) : "memory");
        }
        __syncwarp();
        if (lane == 0) mbar_arrive(bars + 8 * (B_FB + wg));
        mbar_wait(bars + 16 * b + 8 * (B_FULL + 1), 0, budget);
      } else {
        wg_fence();
        rs<0, 0, 0, 14>(d, acc, a); batch_mid(c, bars + 16 * b);
        if constexpr (b == 0) { if (LNS == 1 || (LNS == 2 && wg == 0)) ln_rest(); }
      }
      mma_hi<0>(c, bs, d, acc, a + 56);
      if constexpr (b == 0) { if (LNS == 1 || (LNS == 2 && wg == 0)) ln_send(); }
      if constexpr (b == 0) {
        PROF_T(56);
        if (wg != n) {
          mbar_wait(bars + 8 * B_VAR, 0, budget);
          asm volatile("ld.shared.v2.f32 {%0, %1}, [%2];" : "=f"(r0), "=f"(r1) : "r"(base + VAR_OFF + (8 * w + g) * 8) : "memory");
        }
      }
      if constexpr (b == 2) {
        mbar_wait(bars + 8 * B_EB, 0, budget);
        mbar_wait(bars + 8 * B_XF, 0, budget);
        mbar_wait(bars + 8 * (B_FB + wg), 0, budget);
      }
      batch_rel_hi(bs); fence_regs(acc); PROF_T(3 + 2 * b);
      uint32_t pk[16];
      if constexpr (b == 1) {
        #pragma unroll
        for (int i = 0; i < 7; i++) {
          pk[2 * i] = pack_bf16(acc[4 * i] * r0, acc[4 * i + 1] * r0);
          pk[2 * i + 1] = pack_bf16(acc[4 * i + 2] * r1, acc[4 * i + 3] * r1);
        }
        pk[14] = pk[15] = (t & 1) ? 0u : 0x3F80u;
      } else {
        const float l0 = r0 * LOG2E, l1 = r1 * LOG2E;
        #pragma unroll
        for (int i = 0; i < 7; i++) {
          pk[2 * i] = pack_bf16(phi(acc[4 * i], r0, l0), phi(acc[4 * i + 1], r0, l0));
          pk[2 * i + 1] = pack_bf16(phi(acc[4 * i + 2], r1, l1), phi(acc[4 * i + 3], r1, l1));
        }
        pk[14] = pk[15] = 0;
      }
      const uint32_t dst = base + (b == 1 ? V_OFF : PK_OFF);
      #pragma unroll
      for (int q = 0; q < 4; q++) stsm4(dst + (tile_off ^ (q * 32)), pk[4 * q], pk[4 * q + 1], pk[4 * q + 2], pk[4 * q + 3]);
      if constexpr (b == 1) fence_async();
    });
    uint32_t h[56];
    undef_regs(h);
    uint32_t hdst = mapa(base + XR2 + wg * SLOT + tid * 16, n ^ 1) - 4096;
    const uint32_t hbar = mapa(bars + 8 * (B_HB + 2 * wg), n ^ 1);
    float nl0 = 0.5f * r0, nl1 = 0.5f * r1;
    auto gate = [&](float (&acc)[32], uint32_t* o, uint32_t hb, int b) {
      hdst += 4096;
      float hv[16];
      #pragma unroll
      for (int i = 0; i < 16; i++) {
        const float x = acc[i] * ((i & 2) ? nl1 : nl0), xu = x * acc[16 + i];
        hv[i] = fmaf(tanh_hw(x), xu, xu);
      }
      #pragma unroll
      for (int i = 0; i < 8; i++) o[i] = pack_bf16(hv[2 * i], hv[2 * i + 1]);
      st_async4(hdst, o[0], o[1], o[2], o[3], hb);
      st_async4(hdst + 2048, o[4], o[5], o[6], o[7], hb);
    };
    uint32_t bs = bars + 16, bf = bars + 48;
    #pragma unroll 1
    for (int b = 3; b < 9; b++) {
      const uint64_t d = d64 + (b & 1) * (SLOT >> 3);
      PROF_S(38 + b);
      tile_wait(c, bf);
      batch_begin(c); PROF_S(2 + 2 * b);
      float acc[32];
      wg_fence();
      rs<1, 0, 0, 14>(d, acc, a); batch_mid(c, bf);
      mma_hi<1>(c, bs, d, acc, a + 56);
      if (b == 4) fence_async();
      if (b == OB) mbar_wait(bars + 8 * B_KVB, 0, budget);
      batch_rel_hi(bs);
      PROF_T(3 + 2 * b);
      bs ^= 16; bf += 16;
      uint32_t* oa = h + 16;
      if (b == OB) {
        wg_fence();
        static_for<0, 4>([&](auto K) { constexpr int k = decltype(K)::value;
          wgmma_ss_n64_nt<desc_lo(PK_OFF + k * 32, 0), desc_lo(KV_OFF + k * 2048, 0)>(oa, d128 + wg * 512, d128, k ? 1 : zero); });
        wg_commit();
        nl0 = __uint_as_float(__float_as_uint(nl0) | zero); nl1 = __uint_as_float(__float_as_uint(nl1) | zero);
      }
      fence_regs(acc);
      gate(acc, h + 48, hbar, b);
      wg_wait<0>();
      if (b == OB) {
        #pragma unroll
        for (int e = 0; e < 32; e++) asm volatile("" : "+r"(oa[e]) :: "memory");
        const uint32_t ln = (hdst >> 4) & 31;
        const int src = ln & ~3;
        const float da0 = rcp(__uint_as_float(__shfl_sync(0xffffffff, oa[28], src)) + 1e-6f), da1 = rcp(__uint_as_float(__shfl_sync(0xffffffff, oa[29], src)) + 1e-6f);
        const float db0 = rcp(__uint_as_float(__shfl_sync(0xffffffff, oa[30], src)) + 1e-6f), db1 = rcp(__uint_as_float(__shfl_sync(0xffffffff, oa[31], src)) + 1e-6f);
        const uint32_t so = base + V_OFF + wg * 8192 + w * 1792 + ln * 4;
        #pragma unroll
        for (int q = 0; q < 7; q++) {
          const bool hd = q < 3 ? false : q > 3 ? true : (ln & 2) != 0;
          const float ia = hd ? da1 : da0, ib = hd ? db1 : db0;
          asm volatile("st.shared.u32 [%0], %1;" :: "r"(so + q * 128), "r"(pack_bf16(__uint_as_float(oa[4 * q]) * ia, __uint_as_float(oa[4 * q + 1]) * ia)) : "memory");
          asm volatile("st.shared.u32 [%0], %1;" :: "r"(so + 896 + q * 128), "r"(pack_bf16(__uint_as_float(oa[4 * q + 2]) * ib, __uint_as_float(oa[4 * q + 3]) * ib)) : "memory");
        }
        __syncwarp();
        warp_arrive(bars + 8 * (B_FB + 2 + wg));
      }
      h_place(h, b - 3);
    }
    uint32_t hp[56];
    const uint32_t hs = hdst - 5 * 4096 - (hbar - (bars + 8 * (B_HB + 2 * wg)));
    {
      const uint64_t d = d64 + 2 * (SLOT >> 4);
      PROF_S(47);
      tile_wait(c, bars + 16 * 9);
      batch_begin(c); PROF_S(20);
      float acc[32];
      wg_fence();
      rs<1, 0, 0, 14>(d, acc, a); batch_mid(c, bars + 16 * 9);
      wg_fence();
      rs<1, 1, 0, 4>(d, acc, a + 56); batch_rel_lo(bars + 16);
      rs<1, 1, 4, 14>(d, acc, a + 56); batch_end(c);
      mbar_wait(bars + 8 * (B_HB + 2 * wg), 0, budget);
      #pragma unroll
      for (int k = 0; k < NE; k++) lds128(hs + k * 2048, hp + 4 * k);
      batch_rel_hi(bars + 16); fence_regs(acc);
      PROF_T(21);
      #pragma unroll
      for (int k = NE; k < 12; k++) lds128(hs + k * 2048, hp + 4 * k);
      gate(acc, h + 48, hbar + 8, 9);
    }
    const int tid2 = ((hs >> 4) & 127) ^ 64, lane2 = tid2 & 31;
    #pragma unroll
    for (int i = 48; i < 56; i++) asm volatile("" : "=r"(hp[i]));
    uint32_t tg;
    bs = bars; bf = bars + 160;
    const uint4* gin = &g_part[r][j][wg][0][tid2];
    asm volatile("" : "+l"(gin));
#define PART_LOAD(V, S) { _Pragma("unroll") for (int q = 0; q < 4; q++) ld_b128(gin + (S) * 512 + q * 128, (V)[4 * q], (V)[4 * q + 1], (V)[4 * q + 2], (V)[4 * q + 3]); }
#define PIDX(e) ((e) >= 24 ? (e) : (e) % 8 == 7 ? 28 + (e) / 8 : (e))
#define PART(V, e) (PIDX(e) & 1 ? bf_hi((V)[PIDX(e) / 2]) : bf_lo((V)[PIDX(e) / 2]))
    const uint32_t pin = hs - wg * (SLOT - 16384);
    auto part_get = [&](uint32_t* pv, const uint4* src) {
      while (__any_sync(0xffffffff, ((pv[3] ^ tg) | (pv[7] ^ tg) | (pv[11] ^ tg) | (pv[15] ^ tg)) > 0xffffu) && budget > 0) {
        #pragma unroll
        for (int q = 0; q < 4; q++) ld_b128(src + q * 128, pv[4 * q], pv[4 * q + 1], pv[4 * q + 2], pv[4 * q + 3]);
        budget -= 64;
      }
    };
    #pragma unroll 1
    for (int i = 0; i < 3; i++) {
      const uint64_t d = d128 + ((i & 1) * (SLOT >> 3) + n);
      uint4* gp = const_cast<uint4*>(gin) + ((j ^ (6 - 2 * i)) - j) * 3072 + i * 512;
      PROF_S(48 + i);
      tile_wait(c, bf);
      batch_begin(c); PROF_S(22 + 2 * i);
      float acc[28];
      wg_fence();
      rs<0, 0, 0, 14>(d, acc, h); batch_mid(c, bf);
      wg_fence();
      rs<0, 1, 0, 4>(d, acc, hp); batch_rel_lo(bs);
      rs<0, 1, 4, 12>(d, acc, hp);
      if (i == 0) {
        mbar_wait(bars + 8 * (B_HB + 2 * wg + 1), 0, budget);
        lds128(hs + 12 * 2048, hp + 48); lds128(hs + 13 * 2048, hp + 52);
      }
      wg_fence();
      rs<0, 1, 12, 14>(d, acc, hp); batch_end(c);
      if (i == 0) {
        warp_arrive(bars + 8 * (B_OF + 1));
        if (wg == 1 && lane2 == 0) mbar_arrive_remote(hbar + 8 * (B_X2 - B_HB - 2));
      }
      asm volatile("ld.shared.u32 %0, [%1];" : "=r"(tg) : "r"(base + EPOCH_OFF + 4) : "memory");
      uint32_t pa[16];
      undef_regs(pa);
      if (QLATE) { batch_rel_hi(bs); PROF_T(23 + 2 * i); }
      if (i == 2) {
        mbar_wait(bars + 8 * (B_QB + wg), 0, budget);
        #pragma unroll
        for (int q = 0; q < 4; q++) lds128(pin + q * 2048, pa + 4 * q);
      }
      if (!QLATE) { batch_rel_hi(bs); PROF_T(23 + 2 * i); }
      fence_regs(acc);
      bs ^= 16; bf += 16;
      #pragma unroll
      for (int e = 0; e < 28; e++) acc[e] *= (e & 2) ? nl1 : nl0;
      if (i == 2) {
        part_get(pa, gp - 1024);
        #pragma unroll
        for (int e = 0; e < 28; e++) acc[e] += PART(pa, e);
      }
      uint32_t pv[16];
      #pragma unroll
      for (int q = 0; q < 3; q++) {
        pv[4 * q] = pack_bf16(acc[8 * q], acc[8 * q + 1]); pv[4 * q + 1] = pack_bf16(acc[8 * q + 2], acc[8 * q + 3]);
        pv[4 * q + 2] = pack_bf16(acc[8 * q + 4], acc[8 * q + 5]); pv[4 * q + 3] = pack_bf16(acc[8 * q + 6], __uint_as_float(tg));
      }
      pv[12] = pack_bf16(acc[24], acc[25]); pv[13] = pack_bf16(acc[26], acc[27]); pv[14] = pack_bf16(acc[7], acc[15]); pv[15] = pack_bf16(acc[23], __uint_as_float(tg));
      if (!(ABL & 1) || budget == 12345) st_b128x4(gp, pv);
    }
    uint32_t sp[14], sq[16], pa[16];
    auto pa_load = [&]() {
      mbar_wait(bars + 8 * (B_PB + 2 * wg), 0, budget);
      #pragma unroll
      for (int q = 0; q < 4; q++) lds128(pin + 8192 + q * 2048, pa + 4 * q);
    };
    {
      uint32_t* acc = a + 56;
      mbar_wait(bars + 8 * (B_OB + wg), 0, budget);
      PROF_S(51);
      tile_wait(c, bars + 16 * 13);
      batch_begin(c); PROF_S(28);
      wg_fence();
      const uint64_t ab = dO + wg * (SLOT >> 4), d = d128 + (2 * (SLOT >> 4) + zero);
      static_for<0, 7>([&](auto K) { constexpr int k = decltype(K)::value;
        wgmma_ss_n112_nt<desc_lo(XR + k * 256, 128), desc_lo(k * 2048, 14336)>(acc, ab, d, k ? 1 : zero); });
      batch_mid(c, bars + 16 * 13);
      wg_fence();
      static_for<0, 2>([&](auto K) { constexpr int k = decltype(K)::value;
        wgmma_ss_n112_nt<desc_lo(XR + (7 + k) * 256, 128), desc_lo(SLOT + k * 2048, 14336)>(acc, ab, d, 1); });
      wg_commit(); wg_wait<1>();
      static_for<2, 7>([&](auto K) { constexpr int k = decltype(K)::value;
        wgmma_ss_n112_nt<desc_lo(XR + (7 + k) * 256, 128), desc_lo(SLOT + k * 2048, 14336)>(acc, ab, d, 1); });
      batch_end(c);
      mbar_wait(bars + 8 * B_X2, 0, budget);
      if (PAE == 1) pa_load();
      wait_release<0>(bars + 8 * (B_SF + wg));
      if (PAE == 2) pa_load();
      #pragma unroll
      for (int e = 0; e < 56; e++) asm volatile("" : "+r"(acc[e]) :: "memory");
      PROF_T(29);
      if (NBR) {
        if (n) {
          #pragma unroll
          for (int e = 0; e < 14; e++) {
            asm volatile("cvt.rn.bf16x2.f32 %0, %1, %2;" : "=r"(sq[e]) : "r"(acc[2 * e + 1]), "r"(acc[2 * e]));
            asm volatile("cvt.rn.bf16x2.f32 %0, %1, %2;" : "=r"(sp[e]) : "r"(acc[2 * e + 29]), "r"(acc[2 * e + 28]));
          }
        } else {
          #pragma unroll
          for (int e = 0; e < 14; e++) {
            asm volatile("cvt.rn.bf16x2.f32 %0, %1, %2;" : "=r"(sp[e]) : "r"(acc[2 * e + 1]), "r"(acc[2 * e]));
            asm volatile("cvt.rn.bf16x2.f32 %0, %1, %2;" : "=r"(sq[e]) : "r"(acc[2 * e + 29]), "r"(acc[2 * e + 28]));
          }
        }
      } else {
        #pragma unroll
        for (int e = 0; e < 14; e++) {
          const uint32_t lo = pack_bf16(__uint_as_float(acc[2 * e]), __uint_as_float(acc[2 * e + 1])), hi = pack_bf16(__uint_as_float(acc[28 + 2 * e]), __uint_as_float(acc[29 + 2 * e]));
          sp[e] = n ? hi : lo; sq[e] = n ? lo : hi;
        }
      }
    }
    {
      float ps[28];
      auto first_two = [&]() {
        if (PAE == 0 && !SFIRST) pa_load();
        const uint32_t sd = hdst - 6 * 4096 + 32768 - wg * (SLOT - 8192), sb = hbar + 8 * (B_SB - B_HB) - 8 * wg;
        #pragma unroll
        for (int q = 0; q < 3; q++) st_async4(sd + q * 2048, sq[4 * q], sq[4 * q + 1], sq[4 * q + 2], sq[4 * q + 3], sb);
        asm volatile("st.async.weak.shared::cluster.mbarrier::complete_tx::bytes.v2.b32 [%0], {%1, %2}, [%3];" :: "r"(sd + 6144), "r"(sq[12]), "r"(sq[13]), "r"(sb) : "memory");
        if (PAE == 0 && SFIRST) pa_load();
        part_get(pa, gin + 512);
        if (!HSUM) {
          #pragma unroll
          for (int e = 0; e < 28; e++) ps[e] = PART(pa, e);
          fence_regs(ps);
        }
        PROF_T(53);
      };
      uint32_t xr[16], pl[16];
      const uint32_t st = base + 2 * SLOT + wg * 8192 + w * 2048;
      auto s_load = [&]() {
        mbar_wait(bars + 8 * (B_SB + wg), 0, budget);
        #pragma unroll
        for (int q = 0; q < 4; q++) lds128(hs + 32768 - wg * (SLOT - 8192) + q * 2048, sq + 4 * q);
      };
      auto x_load2 = [&]() {
        const uint32_t xa = base + XR + 8192 + wg * 8192 + w * 2048 + (lane2 >> 3) * 128 + (((((lane2 & 7) + n) & 7) ^ (lane2 >> 3)) << 4);
        mbar_wait(bars + 8 * B_XB, 1, budget);
        #pragma unroll
        for (int it = 0; it < 4; it++) lds128((xa + it * 512) ^ ((it & 1) * 64), xr + 4 * it);
      };
      auto last_load = [&]() {
        if (LALL & 1) s_load();
        if (LALL & 2) x_load2();
        mbar_wait(bars + 8 * (B_PB + 2 * wg + 1), 0, budget);
        #pragma unroll
        for (int q = 0; q < 4; q++) lds128(hs - 57344 + wg * (57344 + 49152 - SLOT) + q * 2048, pl + 4 * q);
      };
      first_two();
      undef_regs(pl);
      if (LALL & 2) undef_regs(xr);
      auto last_add = [&]() {
        part_get(pl, gin + 1024);
        PROF_T(59);
        #pragma unroll
        for (int e = 0; e < 28; e++) ps[e] += PART(pl, e);
        fence_regs(ps);
      };
      auto place = [&](const int at) {
        constexpr int l0 = OWN & 3, l1 = (OWN >> 2) & 3, a0 = (OWN >> 4) & 3, a1 = (OWN >> 6) & 3;
        if (l0 == at && l1 == at) last_load(); else if ((l0 == at && wg == 0) || (l1 == at && wg == 1)) last_load();
        if (a0 == at && a1 == at) last_add(); else if ((a0 == at && wg == 0) || (a1 == at && wg == 1)) last_add();
      };
      float f[28];
      const uint64_t d = d128 + (n - zero);
      tile_wait(c, bars + 16 * 14);
      PROF_S(52);
      batch_begin(c); PROF_S(30);
      wg_fence();
      rs<0, 0, 0, 14>(d, f, h);
      wg_commit();
      place(0);
      mbar_wait(bars + 16 * 14 + 8 * (B_FULL + 1), 0, budget);
      wg_fence();
      rs<0, 1, 0, QK>(d, f, hp);
      wg_commit();
      place(1);
      if (QW) wg_wait<1>(); else wg_fence();
      rs<0, 1, QK, 14>(d, f, hp);
      wg_commit();
      PROF_T(33);
      if (wg == 0) bar_arrive(2, 256);
      place(2);
      if (!(LALL & 1)) s_load();
      if (!(LALL & 2)) x_load2();
      const uint32_t so = st + ((lane2 & 7) + ((lane2 >> 3) & 1) * 8) * 128 + (((lane2 >> 4) ^ (lane2 & 7)) << 4);
      const uint32_t ro = (lane2 >> 3) * 128 + (((lane2 & 7) ^ (lane2 >> 3)) << 4), rd = st + ro;
      const uint32_t xpred = (lane2 & 7) < 7;
      uint4* op = out + ((128 * r + 64 * wg + 16 * w + (lane2 >> 3)) * 56 + 7 * j + (lane2 & 7));
      asm volatile("" : "+l"(op));
      PROF_T(54);
      wg_wait<0>(); fence_regs(f); PROF_T(31);
      uint32_t y[16];
      #pragma unroll
      for (int i = 0; i < 14; i++) {
        const float nl = (i & 1) ? nl1 : nl0, u0 = fmaf(f[2 * i], nl, ps[2 * i]), u1 = fmaf(f[2 * i + 1], nl, ps[2 * i + 1]);
        const uint32_t sa = add_bf16x2(sp[i], sq[i]);
        y[i] = pack_bf16(fmaf(tanh_hw(u0), u0, u0) * bf_lo(sa), fmaf(tanh_hw(u1), u1, u1) * bf_hi(sa));
      }
      y[14] = y[12]; y[15] = y[13];
      #pragma unroll
      for (int q = 0; q < 4; q++) stsm4(so ^ (q * 32), y[4 * q], y[4 * q + 1], y[4 * q + 2], y[4 * q + 3]);
      __syncwarp();
      uint32_t v[16];
      #pragma unroll
      for (int it = 0; it < 4; it++) lds128((rd + it * 512) ^ ((it & 1) * 64), v + 4 * it);
      #pragma unroll
      for (int it = 0; it < 4; it++)
        asm volatile("{\n.reg .pred p;\nsetp.ne.b32 p, %5, 0;\n@p st.global.v4.u32 [%0], {%1, %2, %3, %4};\n}" :: "l"(op + it * 224),
          "r"(add_bf16x2(xr[4 * it], v[4 * it])), "r"(add_bf16x2(xr[4 * it + 1], v[4 * it + 1])), "r"(add_bf16x2(xr[4 * it + 2], v[4 * it + 2])), "r"(add_bf16x2(xr[4 * it + 3], v[4 * it + 3])), "r"(xpred) : "memory");
      PROF_T(32);
    }
  }
}

typedef CUresult (*PFN_encodeTiled_t)(CUtensorMap*, CUtensorMapDataType, cuuint32_t, void*, const cuuint64_t*, const cuuint64_t*, const cuuint32_t*,
                                      const cuuint32_t*, CUtensorMapInterleave, CUtensorMapSwizzle, CUtensorMapL2promotion, CUtensorMapFloatOOBfill);
static void make_map(PFN_encodeTiled_t enc, CUtensorMap* m, const void* ptr, uint64_t cols, uint64_t rows, uint32_t bc, uint32_t br, CUtensorMapSwizzle sw) {
  cuuint64_t gd[2] = {cols, rows}; cuuint64_t gs[1] = {cols * 2};
  cuuint32_t bd[2] = {bc, br}; cuuint32_t es[2] = {1, 1};
  enc(m, CU_TENSOR_MAP_DATA_TYPE_BFLOAT16, 2, const_cast<void*>(ptr), gd, gs, bd, es, CU_TENSOR_MAP_INTERLEAVE_NONE, sw,
      CU_TENSOR_MAP_L2_PROMOTION_L2_128B, CU_TENSOR_MAP_FLOAT_OOB_FILL_NONE);
}

extern "C" void kernel_launch(void* const* d_in, const int* in_sizes, int n_in, void* d_out, int out_size) {
  (void)in_sizes; (void)n_in; (void)out_size;
  void* fn = nullptr; cudaDriverEntryPointQueryResult st;
  cudaGetDriverEntryPoint("cuTensorMapEncodeTiled", &fn, cudaEnableDefault, &st);
  PFN_encodeTiled_t enc = (PFN_encodeTiled_t)fn;
  Maps m;
  {
    cuuint64_t gd[3] = {64, 2048, 7}; cuuint64_t gs[2] = {896, 128};
    cuuint32_t bd[3] = {64, 64, 2}; cuuint32_t es[3] = {1, 1, 1};
    enc(&m.x2, CU_TENSOR_MAP_DATA_TYPE_BFLOAT16, 3, d_in[0], gd, gs, bd, es, CU_TENSOR_MAP_INTERLEAVE_NONE, CU_TENSOR_MAP_SWIZZLE_128B,
        CU_TENSOR_MAP_L2_PROMOTION_L2_128B, CU_TENSOR_MAP_FLOAT_OOB_FILL_NONE);
  }
  make_map(enc, &m.x, d_in[0], 448, 2048, 64, 64, CU_TENSOR_MAP_SWIZZLE_128B);
  make_map(enc, &m.qkv, d_in[1], 1344, 448, 64, 112, CU_TENSOR_MAP_SWIZZLE_128B);
  make_map(enc, &m.wo, d_in[2], 448, 448, 64, 112, CU_TENSOR_MAP_SWIZZLE_128B);
  make_map(enc, &m.w1, d_in[4], 1792, 448, 32, 224, CU_TENSOR_MAP_SWIZZLE_64B);
  make_map(enc, &m.w3, d_in[5], 1792, 448, 32, 224, CU_TENSOR_MAP_SWIZZLE_64B);
  make_map(enc, &m.w2, d_in[6], 448, 1792, 64, 224, CU_TENSOR_MAP_SWIZZLE_128B);
  constexpr int SMEM_ALL = SMEM_BYTES;
  cudaFuncSetAttribute(fused_kernel, cudaFuncAttributeMaxDynamicSharedMemorySize, SMEM_ALL);
  fused_kernel<<<128, 384, SMEM_ALL, cudaStreamPerThread>>>(m, (uint4*)d_out,
    (uint64_t)HI128 << 32 | SB16, (uint64_t)HI64 << 32 | SB16, (uint64_t)HI_O << 32 | SB16, 0);
}
```
